```python
import torch

def _softmax(x, axis=-1):
    return torch.softmax(x, dim=axis)
def _gelu(x):
    return torch.nn.functional.gelu(x, approximate="tanh")
def _silu(x):
    return torch.nn.functional.silu(x)
def _sigmoid(x):
    return torch.sigmoid(x)
def _layernorm(x, axis=-1, eps=1e-5):
    m = x.mean(dim=axis, keepdim=True)
    v = x.var(dim=axis, keepdim=True, unbiased=False)
    return (x - m) / torch.sqrt(v + eps)
def _scatter_add(tgt, idx, src, axis=0):
    return tgt.clone().index_add_(axis, idx, src)
def _segment_sum(src, seg, n):
    out = torch.zeros((n,) + src.shape[1:], dtype=src.dtype)
    return out.index_add_(0, seg, src)
def _pad(x, pw):
    flat = tuple(v for pair in reversed(pw) for v in pair)
    return torch.nn.functional.pad(x, flat)

kernel_name = 'standalone__gqa_block_cached__sampling'

def setup_inputs():

    _w = (lambda a: (lambda t: t.to(torch.bfloat16) if t.is_floating_point() else t)(torch.as_tensor(a)))
    B, Sq, D = 8, 4, 512
    Hq, Hkv, Sk, Dh = 32, 8, 2048, 128
    assert Hq % Hkv == 0, (Hq, Hkv)
    return {
        "x": _w((lambda *s: torch.randn(*s, dtype=torch.bfloat16) * 0.8)(B, Sq, D)),
        "k_cache": _w((lambda *s: torch.randn(*s, dtype=torch.bfloat16) * 0.8)(B, Hkv, Sk, Dh)),
        "v_cache": _w((lambda *s: torch.randn(*s, dtype=torch.bfloat16) * 0.05)(B, Hkv, Sk, Dh)),
        "wq": _w((lambda *s: torch.randn(*s, dtype=torch.bfloat16) * 0.8)(D, Hq * Dh) * (D ** -0.5)),
        "wo": _w((lambda *s: torch.randn(*s, dtype=torch.bfloat16) * 0.05)(Hq * Dh, D) * ((Hq * Dh) ** -0.5)),
    }

def reference(x, k_cache, v_cache, wq, wo):
    B, Sq, D = x.shape
    Hq, Dh = 32, 128
    Hkv = k_cache.shape[1]
    rep = Hq // Hkv
    q = (lambda x, *d: x.permute(*d))((x @ wq).reshape(B, Sq, Hq, Dh), 0, 2, 1, 3)
    k = (lambda x, n, axis: torch.repeat_interleave(x, n, dim=axis))(k_cache, rep, axis=1)
    v = (lambda x, n, axis: torch.repeat_interleave(x, n, dim=axis))(v_cache, rep, axis=1)
    scores = torch.einsum("bhqd,bhkd->bhqk", q, k) * (Dh ** -0.5)
    p = _softmax(scores, axis=-1)
    o = torch.einsum("bhqk,bhkd->bhqd", p, v)
    return (lambda x, *d: x.permute(*d))(o, 0, 2, 1, 3).reshape(B, Sq, Hq * Dh) @ wo
```

```cpp
#include <cuda_runtime.h>
#include <cuda_bf16.h>
#include <cuda.h>
#include <stdint.h>

namespace gqa {

#define PA 2400
#define PT 655
#define GA 300
#define GB 307
#define D0 900
#define D1 800
#define QDELAY 800
constexpr int NCTA = 128;
constexpr int NT = 16;
constexpr int NST = 13;
constexpr int NST0 = 10;
constexpr int WIN0 = 3;
constexpr int WIN = 4;
constexpr int WSW = 8;
constexpr int KA = 2;
constexpr int NP = 4;
constexpr int STAGE = 16384;

constexpr int OFF_WQ = NST0 * STAGE;
constexpr int OFF_X = OFF_WQ + 32768;
constexpr int OFF_QRED = OFF_X;
constexpr int OFF_WO = ((2 * NT) % NST) * STAGE;
constexpr int OFF_P = NST * STAGE;
constexpr int OFF_ORECV = (((2 * NT) % NST) + 3) * STAGE;
constexpr int OFF_ALPHA = OFF_P + NP * 2048;
constexpr int OFF_WMAX = OFF_ALPHA + NP * 64;
constexpr int OFF_LSUM = OFF_WMAX + 512;
constexpr int OFF_MROW = OFF_LSUM + 256;
constexpr int OFF_STAT = OFF_MROW + 64;
constexpr int OFF_F = OFF_STAT + 128;
constexpr int OFF_PRED = (((2 * NT) % NST) + 2) * STAGE;
constexpr int OFF_BAR = (NST + 1) * STAGE;
constexpr int BAR_FULL = OFF_BAR;
constexpr int BAR_EMPTY = BAR_FULL + 8 * NST;
constexpr int BAR_PFULL = BAR_EMPTY + 8 * NST;
constexpr int BAR_PEMPTY = BAR_PFULL + 8 * NP;
constexpr int BAR_W = BAR_PEMPTY + 8 * NP;
constexpr int BAR_STAT = BAR_W + 8;
constexpr int BAR_F = BAR_STAT + 8;
constexpr int BAR_O = BAR_F + 8;
constexpr int BAR_G = BAR_O + 32;
constexpr int BAR_D = BAR_G + 32;
constexpr int OFF_TS = OFF_BAR + 416;
constexpr int SMEM_BYTES = OFF_BAR + 1024;
static_assert(OFF_F + 64 <= OFF_BAR, "scratch overflows its slot");
static_assert(BAR_D + 8 <= OFF_TS, "barriers overflow");
static_assert((2 * NT) % NST + 3 < NST, "wo / partial slots must not wrap");
static_assert(SMEM_BYTES <= 232448, "too much shared memory");

struct Scratch {
    uint4 q[32 * 4 * 8 * 16];
    uint4 o[32 * 4 * 8 * 16];
    uint4 p[128 * 8 * 32];
    unsigned epoch;
};
__device__ Scratch g_scr;

#define STAMP(i)
#define STAMP2(i)

__device__ __forceinline__ void mbar_init(uint32_t bar, uint32_t cnt) {
    asm volatile("mbarrier.init.shared::cta.b64 [%0], %1;" ::"r"(bar), "r"(cnt) : "memory");
}
__device__ __forceinline__ void mbar_expect_tx(uint32_t bar, uint32_t bytes) {
    asm volatile("mbarrier.arrive.expect_tx.shared::cta.b64 _, [%0], %1;" ::"r"(bar), "r"(bytes) : "memory");
}
__device__ __forceinline__ void mbar_arrive(uint32_t bar) {
    asm volatile("mbarrier.arrive.shared::cta.b64 _, [%0];" ::"r"(bar) : "memory");
}
__device__ __forceinline__ bool mbar_try(uint32_t bar, uint32_t parity) {
    uint32_t ok;
    asm volatile("{\n.reg .pred p;\nmbarrier.try_wait.parity.shared::cta.b64 p, [%1], %2;\nselp.u32 %0, 1, 0, p;\n}"
                 : "=r"(ok) : "r"(bar), "r"(parity) : "memory");
    return ok;
}
__device__ __forceinline__ bool mbar_test(uint32_t bar, uint32_t parity) {
    uint32_t ok;
    asm volatile("{\n.reg .pred p;\nmbarrier.test_wait.parity.shared::cta.b64 p, [%1], %2;\nselp.u32 %0, 1, 0, p;\n}"
                 : "=r"(ok) : "r"(bar), "r"(parity) : "memory");
    return ok;
}
__device__ __forceinline__ void mbar_wait(uint32_t bar, uint32_t parity) {
#pragma unroll 1
    for (int i = 0; !mbar_try(bar, parity); i++)
        if (i > (1 << 20)) __trap();
}
__device__ __forceinline__ void tma2d(uint32_t dst, const CUtensorMap* m, int c0, int c1, uint32_t bar) {
    asm volatile("cp.async.bulk.tensor.2d.shared::cluster.global.mbarrier::complete_tx::bytes [%0], [%1, {%3, %4}], [%2];"
                 ::"r"(dst), "l"(m), "r"(bar), "r"(c0), "r"(c1) : "memory");
}
__device__ __forceinline__ void tma3d(uint32_t dst, const CUtensorMap* m, int c0, int c1, int c2, uint32_t bar) {
    asm volatile("cp.async.bulk.tensor.3d.shared::cluster.global.mbarrier::complete_tx::bytes [%0], [%1, {%3, %4, %5}], [%2];"
                 ::"r"(dst), "l"(m), "r"(bar), "r"(c0), "r"(c1), "r"(c2) : "memory");
}
__device__ __forceinline__ void tma3d_hint(uint32_t dst, const CUtensorMap* m, int c0, int c1, int c2, uint32_t bar, uint64_t pol) {
    asm volatile("cp.async.bulk.tensor.3d.shared::cluster.global.mbarrier::complete_tx::bytes.L2::cache_hint [%0], [%1, {%3, %4, %5}], [%2], %6;"
                 ::"r"(dst), "l"(m), "r"(bar), "r"(c0), "r"(c1), "r"(c2), "l"(pol) : "memory");
}
__device__ __forceinline__ void ldsm4(uint32_t (&r)[4], uint32_t addr) {
    asm volatile("ldmatrix.sync.aligned.m8n8.x4.shared.b16 {%0,%1,%2,%3}, [%4];"
                 : "=r"(r[0]), "=r"(r[1]), "=r"(r[2]), "=r"(r[3]) : "r"(addr) : "memory");
}
__device__ __forceinline__ void ldsm4t(uint32_t (&r)[4], uint32_t addr) {
    asm volatile("ldmatrix.sync.aligned.m8n8.x4.trans.shared.b16 {%0,%1,%2,%3}, [%4];"
                 : "=r"(r[0]), "=r"(r[1]), "=r"(r[2]), "=r"(r[3]) : "r"(addr) : "memory");
}
__device__ __forceinline__ void mma(float (&c)[4], const uint32_t (&a)[4], uint32_t b0, uint32_t b1) {
    asm volatile("mma.sync.aligned.m16n8k16.row.col.f32.bf16.bf16.f32 {%0,%1,%2,%3}, {%4,%5,%6,%7}, {%8,%9}, {%0,%1,%2,%3};"
                 : "+f"(c[0]), "+f"(c[1]), "+f"(c[2]), "+f"(c[3])
                 : "r"(a[0]), "r"(a[1]), "r"(a[2]), "r"(a[3]), "r"(b0), "r"(b1));
}
__device__ __forceinline__ uint32_t pack_bf16(float lo, float hi) {
    uint32_t r;
    asm("cvt.rn.bf16x2.f32 %0, %1, %2;" : "=r"(r) : "f"(hi), "f"(lo));
    return r;
}
__device__ __forceinline__ float ex2(float x) {
    float y;
    asm("ex2.approx.ftz.f32 %0, %1;" : "=f"(y) : "f"(x));
    return y;
}
__device__ __forceinline__ void sts128(uint32_t addr, uint32_t a, uint32_t b, uint32_t c, uint32_t d) {
    asm volatile("st.shared.v4.b32 [%0], {%1,%2,%3,%4};" ::"r"(addr), "r"(a), "r"(b), "r"(c), "r"(d) : "memory");
}
__device__ __forceinline__ void sts128f(uint32_t addr, float a, float b, float c, float d) {
    asm volatile("st.shared.v4.f32 [%0], {%1,%2,%3,%4};" ::"r"(addr), "f"(a), "f"(b), "f"(c), "f"(d) : "memory");
}
__device__ __forceinline__ void sts32f(uint32_t addr, float a) {
    asm volatile("st.shared.f32 [%0], %1;" ::"r"(addr), "f"(a) : "memory");
}
__device__ __forceinline__ void lds128(uint32_t (&r)[4], uint32_t addr) {
    asm volatile("ld.shared.v4.b32 {%0,%1,%2,%3}, [%4];" : "=r"(r[0]), "=r"(r[1]), "=r"(r[2]), "=r"(r[3]) : "r"(addr) : "memory");
}
__device__ __forceinline__ float4 lds128f(uint32_t addr) {
    float4 v;
    asm volatile("ld.shared.v4.f32 {%0,%1,%2,%3}, [%4];" : "=f"(v.x), "=f"(v.y), "=f"(v.z), "=f"(v.w) : "r"(addr) : "memory");
    return v;
}
__device__ __forceinline__ float lds32f(uint32_t addr) {
    float v;
    asm volatile("ld.shared.f32 %0, [%1];" : "=f"(v) : "r"(addr) : "memory");
    return v;
}
__device__ __forceinline__ void bar_sync(int id, int n) { asm volatile("bar.sync %0, %1;" ::"r"(id), "r"(n) : "memory"); }
template <typename T> __device__ __forceinline__ T* pin(T* p) { asm volatile("" : "+l"(p)); return p; }
__device__ __forceinline__ uint32_t pin(uint32_t v) { asm volatile("" : "+r"(v)); return v; }

struct Pkt {
    uint64_t lo, hi;
    __device__ __forceinline__ uint32_t w0() const { return (uint32_t)lo; }
    __device__ __forceinline__ uint32_t w1() const { return (uint32_t)(lo >> 32); }
    __device__ __forceinline__ uint32_t w2() const { return (uint32_t)hi; }
    __device__ __forceinline__ uint32_t w3() const { return (uint32_t)(hi >> 32); }
    __device__ __forceinline__ uint32_t bad(uint32_t tag) const {
        uint32_t r;
        asm("lop3.b32 %0, %1, %2, %3, 0x7E;" : "=r"(r) : "r"(w0()), "r"(w2()), "r"(tag));
        return r;
    }
};
__device__ __forceinline__ void pkt_store(uint4* p, uint32_t a, uint32_t b, uint32_t c, uint32_t d, uint32_t tag) {
    a = (a & ~1u) | tag;
    c = (c & ~1u) | tag;
    asm volatile("{\n.reg .b64 lo, hi;\nmov.b64 lo, {%1,%2};\nmov.b64 hi, {%3,%4};\n"
                 "st.relaxed.gpu.global.v2.b64 [%0], {lo, hi};\n}" ::"l"(p), "r"(a), "r"(b), "r"(c), "r"(d) : "memory");
}
__device__ __forceinline__ void pkt_load(Pkt& v, const uint4* p) {
    asm volatile("ld.relaxed.gpu.global.v2.b64 {%0, %1}, [%2];" : "=l"(v.lo), "=l"(v.hi) : "l"(p) : "memory");
}
__device__ __forceinline__ void pkt_reload(Pkt& v, const uint4* p, uint32_t bad) {
    asm volatile("{\n.reg .pred p;\n.reg .b32 t;\nand.b32 t, %3, 1;\nsetp.ne.u32 p, t, 0;\n"
                 "@p ld.relaxed.gpu.global.v2.b64 {%0, %1}, [%2];\n}"
                 : "+l"(v.lo), "+l"(v.hi) : "l"(p), "r"(bad) : "memory");
}
__device__ __forceinline__ uint32_t or3(uint32_t a, uint32_t b, uint32_t c) {
    uint32_t r;
    asm("lop3.b32 %0, %1, %2, %3, 0xFE;" : "=r"(r) : "r"(a), "r"(b), "r"(c));
    return r;
}
template <int N, int N0, int S0, int S1>
__device__ __forceinline__ void pkt_issue(Pkt (&v)[N], const uint4* p) {
#pragma unroll
    for (int i = 0; i < N; i++) pkt_load(v[i], p + (i / N0) * S1 + (i % N0) * S0);
}
template <int N, int N0, int S0, int S1>
__device__ __forceinline__ void pkt_poll(Pkt (&v)[N], const uint4* p, uint32_t tag) {
    static_assert(N == 1 || N == 8, "");
#pragma unroll 1
    for (int it = 0;; it++) {
        uint32_t b[N];
#pragma unroll
        for (int i = 0; i < N; i++) b[i] = v[i].bad(tag);
        uint32_t bad = b[0];
        if (N == 8) bad = or3(or3(b[0], b[1 % N], b[2 % N]), or3(b[3 % N], b[4 % N], b[5 % N]), b[6 % N] | b[7 % N]);
        if (!__any_sync(0xffffffffu, bad & 1u)) break;
        if (it > (1 << 20)) __trap();
#pragma unroll
        for (int i = 0; i < N; i++) pkt_reload(v[i], p + (i / N0) * S1 + (i % N0) * S0, b[i]);
    }
}

__device__ __forceinline__ uint32_t now_ns() {
    uint32_t t;
    asm volatile("mov.u32 %0, %%globaltimer_lo;" : "=r"(t));
    return t;
}
__device__ __forceinline__ void wait_until(uint32_t t) {
#pragma unroll 1
    for (int i = 0; (int)(now_ns() - t) < 0 && i < (1 << 16); i++) {}
}

__global__ void __cluster_dims__(2, 1, 1) __launch_bounds__(288, 1)
gqa_kernel(const __grid_constant__ CUtensorMap tmK, const __grid_constant__ CUtensorMap tmV,
           const __grid_constant__ CUtensorMap tmX, const __grid_constant__ CUtensorMap tmWq,
           const __grid_constant__ CUtensorMap tmWo, __nv_bfloat16* __restrict__ out, uint32_t slot_ns, uint32_t zero) {
    extern __shared__ __align__(1024) uint8_t smem_raw[];
    const uint32_t sb = pin((uint32_t)__cvta_generic_to_shared(smem_raw));
    if (threadIdx.x == 0) {
        mbar_init(sb + BAR_W, 1);
        asm volatile("fence.mbarrier_init.release.cluster;" ::: "memory");
        mbar_expect_tx(sb + BAR_W, 65536);
        tma2d(sb + OFF_WQ, &tmWq, blockIdx.x * 32, 0, sb + BAR_W);
        tma2d(sb + OFF_WQ + 16384, &tmWq, blockIdx.x * 32, 256, sb + BAR_W);
        tma3d(sb + OFF_X, &tmX, 0, 0, 0, sb + BAR_W);
    }
    const int warp = __shfl_sync(0xffffffffu, threadIdx.x >> 5, 0), lane = pin(threadIdx.x & 31);
    const int cta = pin(blockIdx.x), rank = cta & 1, bh = cta >> 1;

    if (warp == 8) {
        const int row0 = bh * 2048 + rank * 64;
        const uint32_t tstart = now_ns();
        uint64_t pol;
        asm volatile("createpolicy.fractional.L2::evict_first.b64 %0, 1.0;" : "=l"(pol));
        auto issue = [&](int n) {
            const bool isv = n >= 2 * NT - KA || (n >= KA && ((n - KA) & 1));
            const int t = n < KA ? n : n >= 2 * NT - KA ? n - NT : isv ? (n - KA) >> 1 : (n + KA) >> 1;
            const int st = n % NST;
            if (n >= 2 * NT) tma2d(sb + st * STAGE, &tmWo, (cta & 15) * 32, (cta >> 4) * 512 + (n - 2 * NT) * 256, sb + BAR_FULL + 8 * st);
            else tma3d_hint(sb + st * STAGE, isv ? &tmV : &tmK, 0, row0 + t * 128, 0, sb + BAR_FULL + 8 * st, pol);
        };
        if (lane == 0) {
            STAMP(0);
            if (sb & 1023) __trap();
#pragma unroll
            for (int i = 0; i < WIN0; i++) mbar_init(sb + BAR_FULL + 8 * i, 1);
            asm volatile("fence.mbarrier_init.release.cluster;" ::: "memory");
#pragma unroll
            for (int n = 0; n < WIN0; n++) {
                mbar_expect_tx(sb + BAR_FULL + 8 * n, STAGE);
                issue(n);
            }
            for (int i = WIN0; i < NST; i++) mbar_init(sb + BAR_FULL + 8 * i, 1);
            for (int i = 0; i < NST; i++) mbar_init(sb + BAR_EMPTY + 8 * i, 4);
            for (int i = 0; i < NP; i++) {
                mbar_init(sb + BAR_PFULL + 8 * i, 4);
                mbar_init(sb + BAR_PEMPTY + 8 * i, 4);
            }
            mbar_init(sb + BAR_STAT, 1);
            mbar_init(sb + BAR_F, 1);
            mbar_init(sb + BAR_D, 4);
            mbar_expect_tx(sb + BAR_STAT, 128);
            for (int i = 0; i < 4; i++) {
                mbar_init(sb + BAR_O + 8 * i, 1);
                mbar_expect_tx(sb + BAR_O + 8 * i, 1024);
                mbar_init(sb + BAR_G + 8 * i, 1);
                mbar_expect_tx(sb + BAR_G + 8 * i, 1024);
            }
            asm volatile("fence.mbarrier_init.release.cluster;" ::: "memory");
            asm volatile("prefetch.tensormap [%0];" ::"l"(&tmWo) : "memory");
        }
        __syncthreads();
        asm volatile("barrier.cluster.arrive.relaxed.aligned;" ::: "memory");
        if (lane == 0) {
            auto wait_free = [&](int n) {
                const int st = n % NST, k = n / NST;
                if (st >= NST0) mbar_wait(sb + BAR_EMPTY + 8 * st, k & 1);
                else if (k) mbar_wait(sb + BAR_EMPTY + 8 * st, (k - 1) & 1);
            };
            const uint32_t t3 = tstart + PA;
#pragma unroll
            for (int n = WIN0; n < 2 * NT + 2; n++) {
                wait_free(n);
                if (n == 2 * NT) wait_free(2 * NT + 2);
                mbar_expect_tx(sb + BAR_FULL + 8 * (n % NST), STAGE);
                if (n != WSW) {
                    const int d = n - (n < WSW ? WIN0 : WIN);
                    mbar_wait(sb + BAR_FULL + 8 * (d % NST), (d / NST) & 1);
                }
                if (n >= WSW) wait_until(t3 + (n < 2 * NT ? (n - 3) * slot_ns : (n == 2 * NT ? GA : GB) * slot_ns / 10));
                issue(n);
                STAMP2(n);
            }
        }
        return;
    }

    unsigned epoch;
    asm volatile("ld.relaxed.gpu.global.u32 %0, [%1];" : "=r"(epoch) : "l"(&g_scr.epoch) : "memory");
    const int g8 = lane >> 2, quad = lane & 3;
    const uint4* const oin = pin(&g_scr.o[((cta >> 4) * 4 + (warp & 3)) * 512 + (warp >> 2) * 64 + lane]);
    uint4* const pout = pin(&g_scr.p[((((warp >> 2) * 2 + (warp & 1)) * 32 + (cta & 15) * 2 + ((warp >> 1) & 1)) * 8 + (cta >> 4)) * 32 +
                                     quad * 8 + g8]);
    const uint4* const pin_ = pin(&g_scr.p[(cta * 8 + g8) * 32 + warp * 4 + quad]);
    __nv_bfloat16* const optr = pin(out + ((cta >> 5) * 8 + (warp >> 1) * 2 + (g8 & 1)) * 512 + (cta & 31) * 16 + (warp & 1) * 4 + quad +
                                    ((g8 >> 1) & 1) * 8);
    __syncthreads();

    {
        const int kq = warp & 3, mt = warp >> 2;
        float c[4][4];
#pragma unroll
        for (int j = 0; j < 4; j++) c[j][0] = c[j][1] = c[j][2] = c[j][3] = 0.f;
        const int ar = mt * 16 + (lane & 15);
        const uint32_t abase = sb + OFF_X + kq * 8192 + ar * 128;
        const int br = lane & 15;
        const uint32_t bbase = sb + OFF_WQ + (kq * 128 + br) * 64;
        if (warp < 4) pkt_store(&g_scr.q[cta * 128 + warp * 32 + lane], 0, 0, 0, 0, epoch & 1);
        mbar_wait(sb + BAR_W, 0);
#pragma unroll
        for (int ks = 0; ks < 8; ks++) {
            uint32_t a[4], b0[4], b1[4];
            ldsm4(a, abase + (ks >> 2) * 4096 + ((((ks & 3) * 2 + (lane >> 4)) ^ (ar & 7)) << 4));
            ldsm4t(b0, bbase + ks * 1024 + (((lane >> 4) ^ ((br >> 1) & 3)) << 4));
            ldsm4t(b1, bbase + ks * 1024 + (((2 + (lane >> 4)) ^ ((br >> 1) & 3)) << 4));
            mma(c[0], a, b0[0], b0[1]);
            mma(c[1], a, b0[2], b0[3]);
            mma(c[2], a, b1[0], b1[1]);
            mma(c[3], a, b1[2], b1[3]);
        }
        bar_sync(1, 256);
        asm volatile("barrier.cluster.arrive.relaxed.aligned;" ::: "memory");
        const uint32_t rb = sb + OFF_QRED + (kq * 2 + mt) * 2048 + lane * 16;
        sts128f(rb, c[0][0], c[0][1], c[1][0], c[1][1]);
        sts128f(rb + 512, c[2][0], c[2][1], c[3][0], c[3][1]);
        sts128f(rb + 1024, c[0][2], c[0][3], c[1][2], c[1][3]);
        sts128f(rb + 1536, c[2][2], c[2][3], c[3][2], c[3][3]);
        bar_sync(1, 256);
    }
    const uint32_t tag = pin((epoch + 1) & 1);

    if (warp < 4) {
        {
            const uint32_t rb = sb + OFF_QRED + warp * 1024 + lane * 16;
            float4 s0 = lds128f(rb), s1 = lds128f(rb + 512);
#pragma unroll
            for (int kq = 1; kq < 4; kq++) {
                float4 t0 = lds128f(rb + kq * 4096), t1 = lds128f(rb + kq * 4096 + 512);
                s0.x += t0.x; s0.y += t0.y; s0.z += t0.z; s0.w += t0.w;
                s1.x += t1.x; s1.y += t1.y; s1.z += t1.z; s1.w += t1.w;
            }
            pkt_store(&g_scr.q[cta * 128 + warp * 32 + lane], pack_bf16(s0.x, s0.y), pack_bf16(s0.z, s0.w),
                      pack_bf16(s1.x, s1.y), pack_bf16(s1.z, s1.w), tag);
            __syncwarp();
            if (lane < NST - NST0) mbar_arrive(sb + BAR_EMPTY + 8 * (NST0 + lane));
        }
        __nanosleep(QDELAY);
        uint32_t q[8][4];
        {
            Pkt v[8];
            const uint4* qp = &g_scr.q[(((bh & 7) * 4 + (lane >> 4)) * 4) * 128 + (bh >> 3) * 16 + (lane & 15)];
            pkt_issue<8, 4, 128, 1024>(v, qp);
            pkt_poll<8, 4, 128, 1024>(v, qp, tag);
#pragma unroll
            for (int dq = 0; dq < 4; dq++) {
                const Pkt a = rank ? v[4 + dq] : v[dq], b = rank ? v[dq] : v[4 + dq];
                q[2 * dq][0] = a.w0();     q[2 * dq][1] = b.w0();     q[2 * dq][2] = a.w1();     q[2 * dq][3] = b.w1();
                q[2 * dq + 1][0] = a.w2(); q[2 * dq + 1][1] = b.w2(); q[2 * dq + 1][2] = a.w3(); q[2 * dq + 1][3] = b.w3();
            }
        }
        if (threadIdx.x == 0) STAMP(3);
        asm volatile("barrier.cluster.wait.acquire.aligned;" ::: "memory");
        constexpr float C = 0.08838834764831845f * 1.4426950408889634f;
        float mc0 = -INFINITY, mc1 = -INFINITY, l0 = 0.f, l1 = 0.f;
        const int key = warp * 16 + (lane >> 4) * 8 + (lane & 7);
        const uint32_t koff = key * 128;
        const int ksel = (lane >> 3) & 1, kx = lane & 7;
        int st = 0;
        uint32_t par = 0;
        pkt_store(pout, 0, 0, 0, 0, tag ^ 1);
#pragma unroll 1
        for (int i = 0; i < NT; i++) {
            const uint32_t kb = sb + st * STAGE + koff;
            float s[2][2][4];
#pragma unroll
            for (int j = 0; j < 4; j++) s[0][0][j] = s[0][1][j] = s[1][0][j] = s[1][1][j] = 0.f;
            mbar_wait(sb + BAR_FULL + 8 * st, par);
#pragma unroll
            for (int ks = 0; ks < 8; ks++) {
                uint32_t b[4];
                ldsm4(b, kb + (ks >> 2) * 8192 + ((((ks & 3) * 2 + ksel) ^ kx) << 4));
                mma(s[ks & 1][0], q[ks], b[0], b[1]);
                mma(s[ks & 1][1], q[ks], b[2], b[3]);
            }
            __syncwarp();
            if (lane == 0) mbar_arrive(sb + BAR_EMPTY + 8 * st);
            st += i < KA ? 1 : 2;
            if (st >= NST) { st -= NST; par ^= 1; }
            float sv[2][4];
#pragma unroll
            for (int j = 0; j < 4; j++) { sv[0][j] = s[0][0][j] + s[1][0][j]; sv[1][j] = s[0][1][j] + s[1][1][j]; }
            float t0 = fmaxf(fmaxf(sv[0][0], sv[0][1]), fmaxf(sv[1][0], sv[1][1]));
            float t1 = fmaxf(fmaxf(sv[0][2], sv[0][3]), fmaxf(sv[1][2], sv[1][3]));
            t0 = fmaxf(t0, __shfl_xor_sync(0xffffffffu, t0, 1));
            t1 = fmaxf(t1, __shfl_xor_sync(0xffffffffu, t1, 1));
            t0 = fmaxf(t0, __shfl_xor_sync(0xffffffffu, t0, 2));
            t1 = fmaxf(t1, __shfl_xor_sync(0xffffffffu, t1, 2));
            const uint32_t wm = sb + OFF_WMAX + (i & 1) * 256 + g8 * 16;
            if (quad == 0) { sts32f(wm + warp * 4, t0); sts32f(wm + 128 + warp * 4, t1); }
            bar_sync(2, 128);
            const float4 w0 = lds128f(wm), w1 = lds128f(wm + 128);
            const float n0 = fmaxf(mc0, fmaxf(fmaxf(w0.x, w0.y), fmaxf(w0.z, w0.w)) * C);
            const float n1 = fmaxf(mc1, fmaxf(fmaxf(w1.x, w1.y), fmaxf(w1.z, w1.w)) * C);
            const float a0 = ex2(mc0 - n0), a1 = ex2(mc1 - n1);
            mc0 = n0; mc1 = n1;
            float p[2][4];
#pragma unroll
            for (int j = 0; j < 2; j++) {
                p[j][0] = ex2(fmaf(sv[j][0], C, -n0)); p[j][1] = ex2(fmaf(sv[j][1], C, -n0));
                p[j][2] = ex2(fmaf(sv[j][2], C, -n1)); p[j][3] = ex2(fmaf(sv[j][3], C, -n1));
            }
            l0 = l0 * a0 + ((p[0][0] + p[0][1]) + (p[1][0] + p[1][1]));
            l1 = l1 * a1 + ((p[0][2] + p[0][3]) + (p[1][2] + p[1][3]));
            const int slot = i % NP;
            if (i >= NP) mbar_wait(sb + BAR_PEMPTY + 8 * slot, (i / NP - 1) & 1);
            sts128(sb + OFF_P + slot * 2048 + warp * 512 + lane * 16, pack_bf16(p[0][0], p[0][1]), pack_bf16(p[0][2], p[0][3]),
                   pack_bf16(p[1][0], p[1][1]), pack_bf16(p[1][2], p[1][3]));
            if (warp == 0 && quad == 0) {
                sts32f(sb + OFF_ALPHA + slot * 64 + g8 * 4, a0);
                sts32f(sb + OFF_ALPHA + slot * 64 + 32 + g8 * 4, a1);
            }
            __syncwarp();
            if (lane == 0) mbar_arrive(sb + BAR_PFULL + 8 * slot);
        }
        l0 += __shfl_xor_sync(0xffffffffu, l0, 1);
        l1 += __shfl_xor_sync(0xffffffffu, l1, 1);
        l0 += __shfl_xor_sync(0xffffffffu, l0, 2);
        l1 += __shfl_xor_sync(0xffffffffu, l1, 2);
        if (quad == 0) {
            sts32f(sb + OFF_LSUM + g8 * 16 + warp * 4, l0);
            sts32f(sb + OFF_LSUM + 128 + g8 * 16 + warp * 4, l1);
            if (warp == 0) { sts32f(sb + OFF_MROW + g8 * 4, mc0); sts32f(sb + OFF_MROW + 32 + g8 * 4, mc1); }
        }
        bar_sync(2, 128);
        if (warp == 0) {
            if (lane < 16) {
                const float4 lv = lds128f(sb + OFF_LSUM + lane * 16);
                const float l = (lv.x + lv.y) + (lv.z + lv.w), m = lds32f(sb + OFF_MROW + lane * 4);
                uint32_t ra, rbar;
                asm("mapa.shared::cluster.u32 %0, %1, %2;" : "=r"(ra) : "r"(sb + OFF_STAT + (lane ^ 8) * 8), "r"(rank ^ 1));
                asm("mapa.shared::cluster.u32 %0, %1, %2;" : "=r"(rbar) : "r"(sb + BAR_STAT), "r"(rank ^ 1));
                asm volatile("st.async.weak.shared::cluster.mbarrier::complete_tx::bytes.v2.f32 [%0], {%1,%2}, [%3];"
                             ::"r"(ra), "f"(m), "f"(l), "r"(rbar) : "memory");
                mbar_wait(sb + BAR_STAT, 0);
                const float pm = lds32f(sb + OFF_STAT + lane * 8), pl = lds32f(sb + OFF_STAT + lane * 8 + 4);
                const float mm = fmaxf(m, pm);
                const float e = ex2(m - mm), pe = ex2(pm - mm);
                sts32f(sb + OFF_F + lane * 4, __fdividef(e, l * e + pl * pe));
            }
            __syncwarp();
            if (lane == 0) mbar_arrive(sb + BAR_F);
        }
        mbar_wait(sb + BAR_D, 0);
    } else {
        const int w = warp - 4;
        asm volatile("barrier.cluster.wait.acquire.aligned;" ::: "memory");
        uint4* const oo = &g_scr.o[(((bh & 7) * 4 + (lane >> 4)) * 4 + w) * 128 + (bh >> 3) * 16 + (lane & 15)];
        uint4* const oout0 = pin(oo + rank * 1024);
        uint4* const oout1 = pin(oo + (rank ^ 1) * 1024);
        const uint32_t la = pin(sb + OFF_ORECV + (w * 32 + lane) * 16), obar = pin(sb + BAR_O + 8 * w);
        uint32_t ra, rbar;
        asm volatile("mapa.shared::cluster.u32 %0, %1, %2;" : "=r"(ra) : "r"(la), "r"(rank ^ 1));
        asm volatile("mapa.shared::cluster.u32 %0, %1, %2;" : "=r"(rbar) : "r"(obar), "r"(rank ^ 1));
        float o[4][4], t[2][4][4];
#pragma unroll
        for (int j = 0; j < 16; j++) (&o[0][0])[j] = (&t[0][0][0])[j] = (&t[1][0][0])[j] = 0.f;
        const uint32_t voff = (w >> 1) * 8192 + (lane & 15) * 128;
        const int vc = (w & 1) * 4 + (lane >> 4), vx = lane & 7;
        const uint32_t v0 = pin(sb + voff + ((vc ^ vx) << 4)), v1 = pin(sb + voff + (((vc + 2) ^ vx) << 4));
        pkt_store(pout, 0, 0, 0, 0, tag ^ 1);
        pkt_store(oout0, 0, 0, 0, 0, tag ^ 1);
        uint32_t p[4][4], b0[4][4], b1[4][4];
        float a0 = 0.f, a1 = 0.f;
        auto load_v = [&](int st) {
#pragma unroll
            for (int j = 0; j < 4; j++) {
                ldsm4t(b0[j], v0 + st * STAGE + j * 2048);
                ldsm4t(b1[j], v1 + st * STAGE + j * 2048);
            }
        };
        auto next_p = [&](int i) {
            const int slot = i % NP;
            mbar_wait(sb + BAR_PFULL + 8 * slot, (i / NP) & 1);
#pragma unroll
            for (int j = 0; j < 4; j++) lds128(p[j], sb + OFF_P + slot * 2048 + j * 512 + lane * 16);
            const float n0 = lds32f(sb + OFF_ALPHA + slot * 64 + g8 * 4), n1 = lds32f(sb + OFF_ALPHA + slot * 64 + 32 + g8 * 4);
            __syncwarp();
            if (lane == 0) mbar_arrive(sb + BAR_PEMPTY + 8 * slot);
#pragma unroll
            for (int j = 0; j < 4; j++) {
                o[j][0] = fmaf(o[j][0], a0, t[0][j][0] + t[1][j][0]); o[j][1] = fmaf(o[j][1], a0, t[0][j][1] + t[1][j][1]);
                o[j][2] = fmaf(o[j][2], a1, t[0][j][2] + t[1][j][2]); o[j][3] = fmaf(o[j][3], a1, t[0][j][3] + t[1][j][3]);
            }
            a0 = n0; a1 = n1;
        };
        auto pv = [&]() {
#pragma unroll
            for (int j = 0; j < 16; j++) (&t[0][0][0])[j] = (&t[1][0][0])[j] = 0.f;
#pragma unroll
            for (int j = 0; j < 4; j++) {
                mma(t[j & 1][0], p[j], b0[j][0], b0[j][1]);
                mma(t[j & 1][1], p[j], b0[j][2], b0[j][3]);
                mma(t[j & 1][2], p[j], b1[j][0], b1[j][1]);
                mma(t[j & 1][3], p[j], b1[j][2], b1[j][3]);
            }
        };
        int st = KA + 1;
        uint32_t par = 0;
#pragma unroll 1
        for (int i = 0; i < NT - 1; i++) {
            mbar_wait(sb + BAR_FULL + 8 * st, par);
            load_v(st);
            next_p(i);
            pv();
            __syncwarp();
            if (lane == 0) mbar_arrive(sb + BAR_EMPTY + 8 * st);
            st += i < NT - KA - 1 ? 2 : 1;
            if (st >= NST) { st -= NST; par ^= 1; }
        }
        constexpr int LST = (2 * NT - 1) % NST, LPAR = ((2 * NT - 1) / NST) & 1;
        const bool landed = mbar_test(sb + BAR_FULL + 8 * LST, LPAR);
        if (landed) load_v(LST);
        next_p(NT - 1);
        mbar_wait(sb + BAR_F, 0);
        const float f0 = lds32f(sb + OFF_F + g8 * 4), f1 = lds32f(sb + OFF_F + 32 + g8 * 4);
        a0 *= f0; a1 *= f1;
#pragma unroll
        for (int j = 0; j < 4; j++) {
            o[j][0] *= a0; o[j][1] *= a0; o[j][2] *= a1; o[j][3] *= a1;
            asm volatile("" : "+f"(o[j][0]), "+f"(o[j][1]), "+f"(o[j][2]), "+f"(o[j][3]));
        }
        if (!landed) {
            mbar_wait(sb + BAR_FULL + 8 * LST, LPAR);
            load_v(LST);
        }
        if (threadIdx.x == 128) STAMP(6);
        auto finish = [&]() {
            pv();
#pragma unroll
            for (int j = 0; j < 4; j++) {
                o[j][0] = fmaf(t[0][j][0] + t[1][j][0], f0, o[j][0]); o[j][1] = fmaf(t[0][j][1] + t[1][j][1], f0, o[j][1]);
                o[j][2] = fmaf(t[0][j][2] + t[1][j][2], f1, o[j][2]); o[j][3] = fmaf(t[0][j][3] + t[1][j][3], f1, o[j][3]);
            }
        };
        auto send = [&]() {
#pragma unroll
            for (int k = 0; k < 4; k++) {
                const int e = k < 2 ? 2 : 0, j = (k & 1) * 2;
                asm volatile("st.async.weak.shared::cluster.mbarrier::complete_tx::bytes.v4.f32 [%0], {%1,%2,%3,%4}, [%5];"
                             ::"r"(ra + k * 2048), "f"(o[j][e]), "f"(o[j][e + 1]), "f"(o[j + 1][e]), "f"(o[j + 1][e + 1]),
                               "r"(rbar + (k < 2 ? 0 : 32)) : "memory");
            }
        };
        auto publish = [&](uint4* dst, int e, const float4& r0, const float4& r1) {
            pkt_store(dst, pack_bf16(o[0][e] + r0.x, o[0][e + 1] + r0.y), pack_bf16(o[1][e] + r0.z, o[1][e + 1] + r0.w),
                      pack_bf16(o[2][e] + r1.x, o[2][e + 1] + r1.y), pack_bf16(o[3][e] + r1.z, o[3][e + 1] + r1.w), tag);
        };
        const bool ha = mbar_test(obar, 0), hb = mbar_test(obar + 32, 0);
        if (ha && hb) {
            const float4 r0 = lds128f(la), r1 = lds128f(la + 2048), r2 = lds128f(la + 4096), r3 = lds128f(la + 6144);
            finish();
            publish(oout0, 0, r0, r1);
            publish(oout1, 2, r2, r3);
            if (threadIdx.x == 128) STAMP(7);
            send();
        } else {
            finish();
            send();
            mbar_wait(obar, 0);
            const float4 r0 = lds128f(la), r1 = lds128f(la + 2048);
            publish(oout0, 0, r0, r1);
            if (threadIdx.x == 128) STAMP(7);
        }
        if (lane == 0) mbar_arrive(sb + BAR_D);
        if (threadIdx.x == 128) STAMP(8);
    }

    {
        const int g = warp & 3, rh = warp >> 2;
        uint32_t a[8][2][4];
        const int kr = (lane >> 4) * 8 + (lane & 7);
        const int wc = (lane >> 3) & 1, wx = (kr >> 1) & 3;
        const uint32_t wb0 = pin(sb + OFF_WO + (g * 128 + kr) * 64 + ((wc ^ wx) << 4));
        const uint32_t wb1 = pin(sb + OFF_WO + (g * 128 + kr) * 64 + (((wc + 2) ^ wx) << 4));
        const uint32_t red = pin(sb + OFF_PRED + rh * 8192 + lane * 16);
        const uint32_t rw = pin(red + g * 512), rr = pin(red + (g & 1) * 4096 + (g >> 1) * 2048);
        const uint32_t wobar = sb + BAR_FULL + 8 * ((2 * NT) % NST + (g >> 1));
        constexpr uint32_t wopar = ((2 * NT) / NST) & 1;
        auto wo_within = [&](uint32_t clks) {
            uint32_t c0, c1;
            bool in;
            asm volatile("mov.u32 %0, %%clock;" : "=r"(c0));
            do {
                in = mbar_test(wobar, wopar);
                asm volatile("mov.u32 %0, %%clock;" : "=r"(c1));
            } while (!in && c1 - c0 < clks);
            return in;
        };
        Pkt v[8];
        const bool in0 = wo_within(D0);
        pkt_issue<8, 4, 128, 32>(v, oin);
        if (!in0) {
#pragma unroll 1
            for (int it = 0; !wo_within(D1); it++) {
                uint32_t b[8];
#pragma unroll
                for (int i = 0; i < 8; i++) b[i] = v[i].bad(tag);
                if (it > (1 << 16)) __trap();
#pragma unroll
                for (int i = 0; i < 8; i++) pkt_reload(v[i], oin + (i >> 2) * 32 + (i & 3) * 128, b[i]);
            }
        }
        if (threadIdx.x == 0) STAMP(9);
        if (threadIdx.x == 64) STAMP(1);
#pragma unroll
        for (int ks = 0; ks < 8; ks++) {
            ldsm4t(a[ks][0], wb0 + ks * 1024);
            ldsm4t(a[ks][1], wb1 + ks * 1024);
        }
        pkt_poll<8, 4, 128, 32>(v, oin, tag | (a[7][1][3] & zero));
        if (threadIdx.x == 0) STAMP(14);
        if (threadIdx.x == 64) STAMP(2);
        if (threadIdx.x == 128) STAMP(4);
        if (threadIdx.x == 192) STAMP(5);
        float c[2][2][2][4];
#pragma unroll
        for (int j = 0; j < 32; j++) (&c[0][0][0][0])[j] = 0.f;
#pragma unroll
        for (int dq = 0; dq < 4; dq++)
#pragma unroll
            for (int t = 0; t < 2; t++) {
                mma(c[t][0][0], a[2 * dq][0], v[t * 4 + dq].w0(), v[t * 4 + dq].w1());
                mma(c[t][1][0], a[2 * dq][1], v[t * 4 + dq].w0(), v[t * 4 + dq].w1());
                mma(c[t][0][1], a[2 * dq + 1][0], v[t * 4 + dq].w2(), v[t * 4 + dq].w3());
                mma(c[t][1][1], a[2 * dq + 1][1], v[t * 4 + dq].w2(), v[t * 4 + dq].w3());
            }
#pragma unroll
        for (int t = 0; t < 2; t++)
#pragma unroll
            for (int mt = 0; mt < 2; mt++)
                sts128f(rw + t * 4096 + mt * 2048, c[t][mt][0][0] + c[t][mt][1][0], c[t][mt][0][1] + c[t][mt][1][1],
                        c[t][mt][0][2] + c[t][mt][1][2], c[t][mt][0][3] + c[t][mt][1][3]);
        bar_sync(3 + rh, 128);
        const float4 s0 = lds128f(rr), s1 = lds128f(rr + 512), s2 = lds128f(rr + 1024), s3 = lds128f(rr + 1536);
        pkt_store(pout, __float_as_uint((s0.x + s1.x) + (s2.x + s3.x)), __float_as_uint((s0.y + s1.y) + (s2.y + s3.y)),
                  __float_as_uint((s0.z + s1.z) + (s2.z + s3.z)), __float_as_uint((s0.w + s1.w) + (s2.w + s3.w)), tag);
        if (threadIdx.x == 0) STAMP(10);
        if (threadIdx.x == 128) STAMP(12);
    }

    {
        Pkt v[1];
        pkt_issue<1, 1, 0, 0>(v, pin_);
        pkt_poll<1, 1, 0, 0>(v, pin_, tag);
        if (threadIdx.x == 0) STAMP(15);
        if (threadIdx.x == 128) STAMP(13);
        const bool hi = g8 & 1, hi2 = g8 & 2;
        float k0 = __uint_as_float(hi ? v[0].w1() : v[0].w0()), k1 = __uint_as_float(hi ? v[0].w3() : v[0].w2());
        k0 += __shfl_xor_sync(0xffffffffu, __uint_as_float(hi ? v[0].w0() : v[0].w1()), 4);
        k1 += __shfl_xor_sync(0xffffffffu, __uint_as_float(hi ? v[0].w2() : v[0].w3()), 4);
        float r = (hi2 ? k1 : k0) + __shfl_xor_sync(0xffffffffu, hi2 ? k0 : k1, 8);
        r += __shfl_xor_sync(0xffffffffu, r, 16);
        if (lane < 16) *optr = __float2bfloat16(r);
        if ((cta | warp | lane) == 0)
            asm volatile("st.relaxed.gpu.global.u32 [%0], %1;" ::"l"(&g_scr.epoch), "r"(epoch + 1) : "memory");
        if (warp >= 4) mbar_wait(sb + BAR_G + 8 * (warp - 4), 0);
        if (threadIdx.x == 0) STAMP(11);
    }
}

typedef CUresult (*EncodeFn)(CUtensorMap*, CUtensorMapDataType, cuuint32_t, void*, const cuuint64_t*, const cuuint64_t*,
                             const cuuint32_t*, const cuuint32_t*, CUtensorMapInterleave, CUtensorMapSwizzle,
                             CUtensorMapL2promotion, CUtensorMapFloatOOBfill);

static void encode(EncodeFn fn, CUtensorMap* m, void* p, int rank, const cuuint64_t* dims, const cuuint64_t* strides,
                   const cuuint32_t* box, CUtensorMapSwizzle sw) {
    const cuuint32_t es[3] = {1, 1, 1};
    fn(m, CU_TENSOR_MAP_DATA_TYPE_BFLOAT16, rank, p, dims, strides, box, es, CU_TENSOR_MAP_INTERLEAVE_NONE, sw,
       CU_TENSOR_MAP_L2_PROMOTION_L2_256B, CU_TENSOR_MAP_FLOAT_OOB_FILL_NONE);
}

}

extern "C" void kernel_launch(void* const* d_in, const int* in_sizes, int n_in, void* d_out, int out_size) {
    using namespace gqa;
    static EncodeFn fn = nullptr;
    static uint32_t slot_ns = PT;
    if (!fn) {
        int dev = 0, khz = 0, bits = 0;
        cudaGetDevice(&dev);
        cudaDeviceGetAttribute(&khz, cudaDevAttrMemoryClockRate, dev);
        cudaDeviceGetAttribute(&bits, cudaDevAttrGlobalMemoryBusWidth, dev);
        if (khz > 0 && bits > 0) slot_ns = (uint32_t)((double)NCTA * STAGE / (0.955 * 2.0 * khz * 1e-6 * (bits / 8)));
        void* p = nullptr;
        cudaDriverEntryPointQueryResult qr;
        cudaGetDriverEntryPoint("cuTensorMapEncodeTiled", &p, cudaEnableDefault, &qr);
        fn = (EncodeFn)p;
        cudaFuncSetAttribute(gqa_kernel, cudaFuncAttributeMaxDynamicSharedMemorySize, SMEM_BYTES);
    }
    CUtensorMap tmK, tmV, tmX, tmWq, tmWo;
    {
        const cuuint64_t dims[3] = {64, 8 * 8 * 2048, 2}, str[2] = {256, 128};
        const cuuint32_t box[3] = {64, 64, 2};
        encode(fn, &tmK, d_in[1], 3, dims, str, box, CU_TENSOR_MAP_SWIZZLE_128B);
        encode(fn, &tmV, d_in[2], 3, dims, str, box, CU_TENSOR_MAP_SWIZZLE_128B);
    }
    {
        const cuuint64_t dims[3] = {64, 32, 8}, str[2] = {1024, 128};
        const cuuint32_t box[3] = {64, 32, 8};
        encode(fn, &tmX, d_in[0], 3, dims, str, box, CU_TENSOR_MAP_SWIZZLE_128B);
    }
    {
        const cuuint64_t dq[2] = {4096, 512}, sq[1] = {8192}, dw[2] = {512, 4096}, sw[1] = {1024};
        const cuuint32_t box[2] = {32, 256};
        encode(fn, &tmWq, d_in[3], 2, dq, sq, box, CU_TENSOR_MAP_SWIZZLE_64B);
        encode(fn, &tmWo, d_in[4], 2, dw, sw, box, CU_TENSOR_MAP_SWIZZLE_64B);
    }
    gqa_kernel<<<NCTA, 288, SMEM_BYTES, cudaStreamPerThread>>>(tmK, tmV, tmX, tmWq, tmWo, (__nv_bfloat16*)d_out, slot_ns, 0u);
}
```

```cpp
#include <cuda_runtime.h>
#include <cuda_bf16.h>
#include <cuda.h>
#include <stdint.h>

namespace gqa {

constexpr int PA_NS = 2250;
constexpr int SLOT_NS = 655;
constexpr int WO_SLOT_A = 300;
constexpr int WO_SLOT_B = 307;
constexpr int Q_DELAY_NS = 800;
constexpr int O_DELAY = 900;
constexpr int O_PERIOD = 800;
constexpr int P_DELAY = 300;
constexpr int PF_BYTES = 8192;

constexpr int NCTA = 128;
constexpr int NT = 16;
constexpr int NST = 13;
constexpr int NST0 = 10;
constexpr int WIN0 = 3;
constexpr int WIN = 6;
constexpr int WSW = 8;
constexpr int KA = 2;
constexpr int NP = 4;
constexpr int STAGE = 16384;

constexpr int OFF_WQ = NST0 * STAGE;
constexpr int OFF_X = OFF_WQ + 32768;
constexpr int OFF_QRED = OFF_X;
constexpr int OFF_WO = ((2 * NT) % NST) * STAGE;
constexpr int OFF_P = NST * STAGE;
constexpr int OFF_ORECV = (((2 * NT) % NST) + 3) * STAGE;
constexpr int OFF_ALPHA = OFF_P + NP * 2048;
constexpr int OFF_WMAX = OFF_ALPHA + NP * 64;
constexpr int OFF_LSUM = OFF_WMAX + 512;
constexpr int OFF_MROW = OFF_LSUM + 256;
constexpr int OFF_STAT = OFF_MROW + 64;
constexpr int OFF_F = OFF_STAT + 128;
constexpr int OFF_PRED = (((2 * NT) % NST) + 2) * STAGE;
constexpr int OFF_BAR = (NST + 1) * STAGE;
constexpr int BAR_FULL = OFF_BAR;
constexpr int BAR_EMPTY = BAR_FULL + 8 * NST;
constexpr int BAR_PFULL = BAR_EMPTY + 8 * NST;
constexpr int BAR_PEMPTY = BAR_PFULL + 8 * NP;
constexpr int BAR_W = BAR_PEMPTY + 8 * NP;
constexpr int BAR_STAT = BAR_W + 8;
constexpr int BAR_F = BAR_STAT + 8;
constexpr int BAR_O = BAR_F + 8;
constexpr int BAR_G = BAR_O + 32;
constexpr int BAR_D = BAR_G + 32;
constexpr int SMEM_BYTES = OFF_BAR + 512;
static_assert(OFF_F + 64 <= OFF_BAR, "scratch overflows its slot");
static_assert(BAR_D + 8 <= SMEM_BYTES, "barriers overflow");
static_assert((2 * NT) % NST + 3 < NST, "wo / partial slots must not wrap");
static_assert(SMEM_BYTES <= 232448, "too much shared memory");

struct Scratch {
    uint4 q[32 * 4 * 8 * 16];
    uint4 o[32 * 4 * 8 * 16];
    uint4 p[128 * 8 * 32];
    unsigned epoch;
};
__device__ Scratch g_scr;

__device__ __forceinline__ void mbar_init(uint32_t bar, uint32_t cnt) {
    asm volatile("mbarrier.init.shared::cta.b64 [%0], %1;" ::"r"(bar), "r"(cnt) : "memory");
}
__device__ __forceinline__ void mbar_expect_tx(uint32_t bar, uint32_t bytes) {
    asm volatile("mbarrier.arrive.expect_tx.shared::cta.b64 _, [%0], %1;" ::"r"(bar), "r"(bytes) : "memory");
}
__device__ __forceinline__ void mbar_arrive(uint32_t bar) {
    asm volatile("mbarrier.arrive.shared::cta.b64 _, [%0];" ::"r"(bar) : "memory");
}
__device__ __forceinline__ bool mbar_try(uint32_t bar, uint32_t parity) {
    uint32_t ok;
    asm volatile("{\n.reg .pred p;\nmbarrier.try_wait.parity.shared::cta.b64 p, [%1], %2;\nselp.u32 %0, 1, 0, p;\n}"
                 : "=r"(ok) : "r"(bar), "r"(parity) : "memory");
    return ok;
}
__device__ __forceinline__ bool mbar_test(uint32_t bar, uint32_t parity) {
    uint32_t ok;
    asm volatile("{\n.reg .pred p;\nmbarrier.test_wait.parity.shared::cta.b64 p, [%1], %2;\nselp.u32 %0, 1, 0, p;\n}"
                 : "=r"(ok) : "r"(bar), "r"(parity) : "memory");
    return ok;
}
__device__ __forceinline__ void mbar_wait(uint32_t bar, uint32_t parity) {
#pragma unroll 1
    for (int i = 0; !mbar_try(bar, parity); i++)
        if (i > (1 << 20)) __trap();
}
__device__ __forceinline__ void tma2d(uint32_t dst, const CUtensorMap* m, int c0, int c1, uint32_t bar) {
    asm volatile("cp.async.bulk.tensor.2d.shared::cluster.global.mbarrier::complete_tx::bytes [%0], [%1, {%3, %4}], [%2];"
                 ::"r"(dst), "l"(m), "r"(bar), "r"(c0), "r"(c1) : "memory");
}
__device__ __forceinline__ void tma3d(uint32_t dst, const CUtensorMap* m, int c0, int c1, int c2, uint32_t bar) {
    asm volatile("cp.async.bulk.tensor.3d.shared::cluster.global.mbarrier::complete_tx::bytes [%0], [%1, {%3, %4, %5}], [%2];"
                 ::"r"(dst), "l"(m), "r"(bar), "r"(c0), "r"(c1), "r"(c2) : "memory");
}
__device__ __forceinline__ void tma3d_hint(uint32_t dst, const CUtensorMap* m, int c0, int c1, int c2, uint32_t bar, uint64_t pol) {
    asm volatile("cp.async.bulk.tensor.3d.shared::cluster.global.mbarrier::complete_tx::bytes.L2::cache_hint [%0], [%1, {%3, %4, %5}], [%2], %6;"
                 ::"r"(dst), "l"(m), "r"(bar), "r"(c0), "r"(c1), "r"(c2), "l"(pol) : "memory");
}
__device__ __forceinline__ void ldsm4(uint32_t (&r)[4], uint32_t addr) {
    asm volatile("ldmatrix.sync.aligned.m8n8.x4.shared.b16 {%0,%1,%2,%3}, [%4];"
                 : "=r"(r[0]), "=r"(r[1]), "=r"(r[2]), "=r"(r[3]) : "r"(addr) : "memory");
}
__device__ __forceinline__ void ldsm4t(uint32_t (&r)[4], uint32_t addr) {
    asm volatile("ldmatrix.sync.aligned.m8n8.x4.trans.shared.b16 {%0,%1,%2,%3}, [%4];"
                 : "=r"(r[0]), "=r"(r[1]), "=r"(r[2]), "=r"(r[3]) : "r"(addr) : "memory");
}
__device__ __forceinline__ void mma(float (&c)[4], const uint32_t (&a)[4], uint32_t b0, uint32_t b1) {
    asm volatile("mma.sync.aligned.m16n8k16.row.col.f32.bf16.bf16.f32 {%0,%1,%2,%3}, {%4,%5,%6,%7}, {%8,%9}, {%0,%1,%2,%3};"
                 : "+f"(c[0]), "+f"(c[1]), "+f"(c[2]), "+f"(c[3])
                 : "r"(a[0]), "r"(a[1]), "r"(a[2]), "r"(a[3]), "r"(b0), "r"(b1));
}
__device__ __forceinline__ uint32_t pack_bf16(float lo, float hi) {
    uint32_t r;
    asm("cvt.rn.bf16x2.f32 %0, %1, %2;" : "=r"(r) : "f"(hi), "f"(lo));
    return r;
}
__device__ __forceinline__ float ex2(float x) {
    float y;
    asm("ex2.approx.ftz.f32 %0, %1;" : "=f"(y) : "f"(x));
    return y;
}
__device__ __forceinline__ void sts128(uint32_t addr, uint32_t a, uint32_t b, uint32_t c, uint32_t d) {
    asm volatile("st.shared.v4.b32 [%0], {%1,%2,%3,%4};" ::"r"(addr), "r"(a), "r"(b), "r"(c), "r"(d) : "memory");
}
__device__ __forceinline__ void sts128f(uint32_t addr, float a, float b, float c, float d) {
    asm volatile("st.shared.v4.f32 [%0], {%1,%2,%3,%4};" ::"r"(addr), "f"(a), "f"(b), "f"(c), "f"(d) : "memory");
}
__device__ __forceinline__ void sts32f(uint32_t addr, float a) {
    asm volatile("st.shared.f32 [%0], %1;" ::"r"(addr), "f"(a) : "memory");
}
__device__ __forceinline__ void lds128(uint32_t (&r)[4], uint32_t addr) {
    asm volatile("ld.shared.v4.b32 {%0,%1,%2,%3}, [%4];" : "=r"(r[0]), "=r"(r[1]), "=r"(r[2]), "=r"(r[3]) : "r"(addr) : "memory");
}
__device__ __forceinline__ float4 lds128f(uint32_t addr) {
    float4 v;
    asm volatile("ld.shared.v4.f32 {%0,%1,%2,%3}, [%4];" : "=f"(v.x), "=f"(v.y), "=f"(v.z), "=f"(v.w) : "r"(addr) : "memory");
    return v;
}
__device__ __forceinline__ float lds32f(uint32_t addr) {
    float v;
    asm volatile("ld.shared.f32 %0, [%1];" : "=f"(v) : "r"(addr) : "memory");
    return v;
}
__device__ __forceinline__ void bar_sync(int id, int n) { asm volatile("bar.sync %0, %1;" ::"r"(id), "r"(n) : "memory"); }
template <typename T> __device__ __forceinline__ T* pin(T* p) { asm volatile("" : "+l"(p)); return p; }
__device__ __forceinline__ uint32_t pin(uint32_t v) { asm volatile("" : "+r"(v)); return v; }

struct Pkt {
    uint64_t lo, hi;
    __device__ __forceinline__ uint32_t w0() const { return (uint32_t)lo; }
    __device__ __forceinline__ uint32_t w1() const { return (uint32_t)(lo >> 32); }
    __device__ __forceinline__ uint32_t w2() const { return (uint32_t)hi; }
    __device__ __forceinline__ uint32_t w3() const { return (uint32_t)(hi >> 32); }
    __device__ __forceinline__ uint32_t bad(uint32_t tag) const {
        uint32_t r;
        asm("lop3.b32 %0, %1, %2, %3, 0x7E;" : "=r"(r) : "r"(w0()), "r"(w2()), "r"(tag));
        return r;
    }
};
__device__ __forceinline__ void pkt_store(uint4* p, uint32_t a, uint32_t b, uint32_t c, uint32_t d, uint32_t tag) {
    a = (a & ~1u) | tag;
    c = (c & ~1u) | tag;
    asm volatile("{\n.reg .b64 lo, hi;\nmov.b64 lo, {%1,%2};\nmov.b64 hi, {%3,%4};\n"
                 "st.relaxed.gpu.global.v2.b64 [%0], {lo, hi};\n}" ::"l"(p), "r"(a), "r"(b), "r"(c), "r"(d) : "memory");
}
__device__ __forceinline__ void pkt_load(Pkt& v, const uint4* p) {
    asm volatile("ld.relaxed.gpu.global.v2.b64 {%0, %1}, [%2];" : "=l"(v.lo), "=l"(v.hi) : "l"(p) : "memory");
}
__device__ __forceinline__ void pkt_reload(Pkt& v, const uint4* p, uint32_t bad) {
    asm volatile("{\n.reg .pred p;\n.reg .b32 t;\nand.b32 t, %3, 1;\nsetp.ne.u32 p, t, 0;\n"
                 "@p ld.relaxed.gpu.global.v2.b64 {%0, %1}, [%2];\n}"
                 : "+l"(v.lo), "+l"(v.hi) : "l"(p), "r"(bad) : "memory");
}
__device__ __forceinline__ uint32_t or3(uint32_t a, uint32_t b, uint32_t c) {
    uint32_t r;
    asm("lop3.b32 %0, %1, %2, %3, 0xFE;" : "=r"(r) : "r"(a), "r"(b), "r"(c));
    return r;
}
__device__ __forceinline__ bool any_bit0(uint32_t x) {
    uint32_t r;
    asm volatile("{\n.reg .pred p, q;\n.reg .b32 t;\nand.b32 t, %1, 1;\nsetp.ne.u32 p, t, 0;\nvote.sync.any.pred q, p, 0xffffffff;\n"
                 "selp.u32 %0, 1, 0, q;\n}" : "=r"(r) : "r"(x));
    return r;
}
template <int N, int N0, int S0, int S1>
__device__ __forceinline__ void pkt_issue(Pkt (&v)[N], const uint4* p) {
#pragma unroll
    for (int i = 0; i < N; i++) pkt_load(v[i], p + (i / N0) * S1 + (i % N0) * S0);
}
template <int N, int N0, int S0, int S1>
__device__ __forceinline__ void pkt_poll(Pkt (&v)[N], const uint4* p, uint32_t tag) {
    static_assert(N == 1 || N == 8, "");
#pragma unroll 1
    for (int it = 0;; it++) {
        uint32_t b[N];
#pragma unroll
        for (int i = 0; i < N; i++) b[i] = v[i].bad(tag);
        uint32_t bad = b[0];
        if (N == 8) bad = or3(or3(b[0], b[1 % N], b[2 % N]), or3(b[3 % N], b[4 % N], b[5 % N]), or3(b[6 % N], b[7 % N], 0u));
        if (!any_bit0(bad)) break;
        if (it > (1 << 20)) __trap();
#pragma unroll
        for (int i = 0; i < N; i++) pkt_reload(v[i], p + (i / N0) * S1 + (i % N0) * S0, b[i]);
    }
}

__device__ __forceinline__ uint32_t now_ns() {
    uint32_t t;
    asm volatile("mov.u32 %0, %%globaltimer_lo;" : "=r"(t));
    return t;
}
__device__ __forceinline__ void spin(uint32_t clks) {
    uint32_t c0, c1;
    asm volatile("mov.u32 %0, %%clock;" : "=r"(c0));
    do { asm volatile("mov.u32 %0, %%clock;" : "=r"(c1)); } while (c1 - c0 < clks);
}
__device__ __forceinline__ void wait_until(uint32_t t) {
#pragma unroll 1
    for (int i = 0; (int)(now_ns() - t) < 0 && i < (1 << 16); i++) {}
}

struct Ptrs { const uint8_t* p[2]; };

__global__ void __cluster_dims__(2, 1, 1) __launch_bounds__(288, 1)
gqa_kernel(const __grid_constant__ Ptrs ptrs, __nv_bfloat16* __restrict__ out, uint32_t slot_ns, uint32_t zero,
           const __grid_constant__ CUtensorMap tmK, const __grid_constant__ CUtensorMap tmV,
           const __grid_constant__ CUtensorMap tmX, const __grid_constant__ CUtensorMap tmWq,
           const __grid_constant__ CUtensorMap tmWo) {
    const uint32_t tstart = now_ns();
    if (threadIdx.x == 32)
        asm volatile("cp.async.bulk.prefetch.L2.global [%0], %1;" ::"l"(ptrs.p[blockIdx.x >> 10] + blockIdx.x * PF_BYTES), "r"(PF_BYTES)
                     : "memory");
    extern __shared__ __align__(1024) uint8_t smem_raw[];
    const uint32_t sb = pin((uint32_t)__cvta_generic_to_shared(smem_raw));
    if (threadIdx.x == 0) {
        mbar_init(sb + BAR_W, 1);
        asm volatile("fence.mbarrier_init.release.cluster;" ::: "memory");
        mbar_expect_tx(sb + BAR_W, 65536);
        tma2d(sb + OFF_WQ, &tmWq, blockIdx.x * 32, 0, sb + BAR_W);
        tma2d(sb + OFF_WQ + 16384, &tmWq, blockIdx.x * 32, 256, sb + BAR_W);
        tma3d(sb + OFF_X, &tmX, 0, 0, 0, sb + BAR_W);
    }
    const int warp = __shfl_sync(0xffffffffu, threadIdx.x >> 5, 0), lane = pin(threadIdx.x & 31);
    const int cta = pin(blockIdx.x), rank = cta & 1, bh = cta >> 1;

    if (warp == 8) {
        const int row0 = bh * 2048 + rank * 64;
        uint64_t pol;
        asm volatile("createpolicy.fractional.L2::evict_first.b64 %0, 1.0;" : "=l"(pol));
        auto issue = [&](int n) {
            const bool isv = n >= 2 * NT - KA || (n >= KA && ((n - KA) & 1));
            const int t = n < KA ? n : n >= 2 * NT - KA ? n - NT : isv ? (n - KA) >> 1 : (n + KA) >> 1;
            const int st = n % NST;
            if (n >= 2 * NT) tma2d(sb + st * STAGE, &tmWo, (cta & 15) * 32, (cta >> 4) * 512 + (n - 2 * NT) * 256, sb + BAR_FULL + 8 * st);
            else tma3d_hint(sb + st * STAGE, isv ? &tmV : &tmK, 0, row0 + t * 128, 0, sb + BAR_FULL + 8 * st, pol);
        };
        if (lane == 0) {
            if (sb & 1023) __trap();
#pragma unroll
            for (int i = 0; i < WIN0; i++) mbar_init(sb + BAR_FULL + 8 * i, 1);
            asm volatile("fence.mbarrier_init.release.cluster;" ::: "memory");
#pragma unroll
            for (int n = 0; n < WIN0; n++) {
                mbar_expect_tx(sb + BAR_FULL + 8 * n, STAGE);
                issue(n);
            }
            for (int i = WIN0; i < NST; i++) mbar_init(sb + BAR_FULL + 8 * i, 1);
            for (int i = 0; i < NST; i++) mbar_init(sb + BAR_EMPTY + 8 * i, 4);
            for (int i = 0; i < NP; i++) {
                mbar_init(sb + BAR_PFULL + 8 * i, 4);
                mbar_init(sb + BAR_PEMPTY + 8 * i, 4);
            }
            mbar_init(sb + BAR_STAT, 1);
            mbar_init(sb + BAR_F, 1);
            mbar_init(sb + BAR_D, 4);
            mbar_expect_tx(sb + BAR_STAT, 128);
            for (int i = 0; i < 4; i++) {
                mbar_init(sb + BAR_O + 8 * i, 1);
                mbar_expect_tx(sb + BAR_O + 8 * i, 1024);
                mbar_init(sb + BAR_G + 8 * i, 1);
                mbar_expect_tx(sb + BAR_G + 8 * i, 1024);
            }
            asm volatile("fence.mbarrier_init.release.cluster;" ::: "memory");
            asm volatile("prefetch.tensormap [%0];" ::"l"(&tmWo) : "memory");
        }
        __syncthreads();
        asm volatile("barrier.cluster.arrive.relaxed.aligned;" ::: "memory");
        if (lane == 0) {
            auto wait_free = [&](int n) {
                const int st = n % NST, k = n / NST;
                if (st >= NST0) mbar_wait(sb + BAR_EMPTY + 8 * st, k & 1);
                else if (k) mbar_wait(sb + BAR_EMPTY + 8 * st, (k - 1) & 1);
            };
            const uint32_t t3 = tstart + PA_NS;
#pragma unroll
            for (int n = WIN0; n < 2 * NT + 2; n++) {
                wait_free(n);
                if (n == 2 * NT) wait_free(2 * NT + 2);
                mbar_expect_tx(sb + BAR_FULL + 8 * (n % NST), STAGE);
                if (n < WSW || n >= WSW + WIN - WIN0) {
                    const int d = n - (n < WSW ? WIN0 : WIN);
                    mbar_wait(sb + BAR_FULL + 8 * (d % NST), (d / NST) & 1);
                }
                if (n >= WSW) wait_until(t3 + (n < 2 * NT ? (n - 3) * slot_ns : (n == 2 * NT ? WO_SLOT_A : WO_SLOT_B) * slot_ns / 10));
                issue(n);
            }
        }
        return;
    }

    unsigned epoch;
    asm volatile("ld.relaxed.gpu.global.u32 %0, [%1];" : "=r"(epoch) : "l"(&g_scr.epoch) : "memory");
    const int g8 = lane >> 2, quad = lane & 3;
    const uint4* const oin = pin(&g_scr.o[((cta >> 4) * 4 + (warp & 3)) * 512 + (warp >> 2) * 64 + lane]);
    uint4* const pout = pin(&g_scr.p[((((warp >> 2) * 2 + (warp & 1)) * 32 + (cta & 15) * 2 + ((warp >> 1) & 1)) * 8 + (cta >> 4)) * 32 +
                                     quad * 8 + g8]);
    const uint4* const pin_ = pin(&g_scr.p[(cta * 8 + (lane >> 3)) * 32 + (warp & 3) * 8 + (lane & 7)]);
    __nv_bfloat16* const optr = pin(out + ((cta >> 5) * 8 + (warp & 3) * 2 + ((lane >> 3) & 1)) * 512 + (cta & 31) * 16 + (lane & 7) +
                                    (lane >> 4) * 8);
    __syncthreads();

    {
        const int kq = warp & 3, mt = warp >> 2;
        float c[4][4];
#pragma unroll
        for (int j = 0; j < 4; j++) c[j][0] = c[j][1] = c[j][2] = c[j][3] = 0.f;
        const int ar = mt * 16 + (lane & 15);
        const uint32_t abase = sb + OFF_X + kq * 8192 + ar * 128;
        const int br = lane & 15;
        const uint32_t bbase = sb + OFF_WQ + (kq * 128 + br) * 64;
        if (warp < 4) pkt_store(&g_scr.q[cta * 128 + warp * 32 + lane], 0, 0, 0, 0, epoch & 1);
        mbar_wait(sb + BAR_W, 0);
#pragma unroll
        for (int ks = 0; ks < 8; ks++) {
            uint32_t a[4], b0[4], b1[4];
            ldsm4(a, abase + (ks >> 2) * 4096 + ((((ks & 3) * 2 + (lane >> 4)) ^ (ar & 7)) << 4));
            ldsm4t(b0, bbase + ks * 1024 + (((lane >> 4) ^ ((br >> 1) & 3)) << 4));
            ldsm4t(b1, bbase + ks * 1024 + (((2 + (lane >> 4)) ^ ((br >> 1) & 3)) << 4));
            mma(c[0], a, b0[0], b0[1]);
            mma(c[1], a, b0[2], b0[3]);
            mma(c[2], a, b1[0], b1[1]);
            mma(c[3], a, b1[2], b1[3]);
        }
        bar_sync(1, 256);
        asm volatile("barrier.cluster.arrive.relaxed.aligned;" ::: "memory");
        const uint32_t rb = sb + OFF_QRED + (kq * 2 + mt) * 2048 + lane * 16;
        sts128f(rb, c[0][0], c[0][1], c[1][0], c[1][1]);
        sts128f(rb + 512, c[2][0], c[2][1], c[3][0], c[3][1]);
        sts128f(rb + 1024, c[0][2], c[0][3], c[1][2], c[1][3]);
        sts128f(rb + 1536, c[2][2], c[2][3], c[3][2], c[3][3]);
        bar_sync(1, 256);
    }
    const uint32_t tag = pin((epoch + 1) & 1);

    if (warp < 4) {
        {
            const uint32_t rb = sb + OFF_QRED + warp * 1024 + lane * 16;
            float4 s0 = lds128f(rb), s1 = lds128f(rb + 512);
#pragma unroll
            for (int kq = 1; kq < 4; kq++) {
                float4 t0 = lds128f(rb + kq * 4096), t1 = lds128f(rb + kq * 4096 + 512);
                s0.x += t0.x; s0.y += t0.y; s0.z += t0.z; s0.w += t0.w;
                s1.x += t1.x; s1.y += t1.y; s1.z += t1.z; s1.w += t1.w;
            }
            pkt_store(&g_scr.q[cta * 128 + warp * 32 + lane], pack_bf16(s0.x, s0.y), pack_bf16(s0.z, s0.w),
                      pack_bf16(s1.x, s1.y), pack_bf16(s1.z, s1.w), tag);
            __syncwarp();
            if (lane < NST - NST0) mbar_arrive(sb + BAR_EMPTY + 8 * (NST0 + lane));
        }
        __nanosleep(Q_DELAY_NS);
        uint32_t q[8][4];
        {
            Pkt v[8];
            const uint4* qp = &g_scr.q[(((bh & 7) * 4 + (lane >> 4)) * 4) * 128 + (bh >> 3) * 16 + (lane & 15)];
            pkt_issue<8, 4, 128, 1024>(v, qp);
            pkt_poll<8, 4, 128, 1024>(v, qp, tag);
#pragma unroll
            for (int dq = 0; dq < 4; dq++) {
                const Pkt a = rank ? v[4 + dq] : v[dq], b = rank ? v[dq] : v[4 + dq];
                q[2 * dq][0] = a.w0();     q[2 * dq][1] = b.w0();     q[2 * dq][2] = a.w1();     q[2 * dq][3] = b.w1();
                q[2 * dq + 1][0] = a.w2(); q[2 * dq + 1][1] = b.w2(); q[2 * dq + 1][2] = a.w3(); q[2 * dq + 1][3] = b.w3();
            }
        }
        asm volatile("barrier.cluster.wait.acquire.aligned;" ::: "memory");
        constexpr float C = 0.08838834764831845f * 1.4426950408889634f;
        float mc0 = -INFINITY, mc1 = -INFINITY, l0 = 0.f, l1 = 0.f;
        const int key = warp * 16 + (lane >> 4) * 8 + (lane & 7);
        const uint32_t koff = key * 128;
        const int ksel = (lane >> 3) & 1, kx = lane & 7;
        int st = 0;
        uint32_t par = 0;
        pkt_store(pout, 0, 0, 0, 0, tag ^ 1);
#pragma unroll 1
        for (int i = 0; i < NT; i++) {
            const uint32_t kb = sb + st * STAGE + koff;
            float s[2][2][4];
#pragma unroll
            for (int j = 0; j < 4; j++) s[0][0][j] = s[0][1][j] = s[1][0][j] = s[1][1][j] = 0.f;
            mbar_wait(sb + BAR_FULL + 8 * st, par);
#pragma unroll
            for (int ks = 0; ks < 8; ks++) {
                uint32_t b[4];
                ldsm4(b, kb + (ks >> 2) * 8192 + ((((ks & 3) * 2 + ksel) ^ kx) << 4));
                mma(s[ks & 1][0], q[ks], b[0], b[1]);
                mma(s[ks & 1][1], q[ks], b[2], b[3]);
            }
            __syncwarp();
            if (lane == 0) mbar_arrive(sb + BAR_EMPTY + 8 * st);
            st += i < KA ? 1 : 2;
            if (st >= NST) { st -= NST; par ^= 1; }
            float sv[2][4];
#pragma unroll
            for (int j = 0; j < 4; j++) { sv[0][j] = s[0][0][j] + s[1][0][j]; sv[1][j] = s[0][1][j] + s[1][1][j]; }
            float t0 = fmaxf(fmaxf(sv[0][0], sv[0][1]), fmaxf(sv[1][0], sv[1][1]));
            float t1 = fmaxf(fmaxf(sv[0][2], sv[0][3]), fmaxf(sv[1][2], sv[1][3]));
            t0 = fmaxf(t0, __shfl_xor_sync(0xffffffffu, t0, 1));
            t1 = fmaxf(t1, __shfl_xor_sync(0xffffffffu, t1, 1));
            t0 = fmaxf(t0, __shfl_xor_sync(0xffffffffu, t0, 2));
            t1 = fmaxf(t1, __shfl_xor_sync(0xffffffffu, t1, 2));
            const uint32_t wm = sb + OFF_WMAX + (i & 1) * 256 + g8 * 16;
            if (quad == 0) { sts32f(wm + warp * 4, t0); sts32f(wm + 128 + warp * 4, t1); }
            bar_sync(2, 128);
            const float4 w0 = lds128f(wm), w1 = lds128f(wm + 128);
            const float n0 = fmaxf(mc0, fmaxf(fmaxf(w0.x, w0.y), fmaxf(w0.z, w0.w)) * C);
            const float n1 = fmaxf(mc1, fmaxf(fmaxf(w1.x, w1.y), fmaxf(w1.z, w1.w)) * C);
            const float a0 = ex2(mc0 - n0), a1 = ex2(mc1 - n1);
            mc0 = n0; mc1 = n1;
            float p[2][4];
#pragma unroll
            for (int j = 0; j < 2; j++) {
                p[j][0] = ex2(fmaf(sv[j][0], C, -n0)); p[j][1] = ex2(fmaf(sv[j][1], C, -n0));
                p[j][2] = ex2(fmaf(sv[j][2], C, -n1)); p[j][3] = ex2(fmaf(sv[j][3], C, -n1));
            }
            l0 = l0 * a0 + ((p[0][0] + p[0][1]) + (p[1][0] + p[1][1]));
            l1 = l1 * a1 + ((p[0][2] + p[0][3]) + (p[1][2] + p[1][3]));
            const int slot = i % NP;
            if (i >= NP) mbar_wait(sb + BAR_PEMPTY + 8 * slot, (i / NP - 1) & 1);
            sts128(sb + OFF_P + slot * 2048 + warp * 512 + lane * 16, pack_bf16(p[0][0], p[0][1]), pack_bf16(p[0][2], p[0][3]),
                   pack_bf16(p[1][0], p[1][1]), pack_bf16(p[1][2], p[1][3]));
            if (warp == 0 && quad == 0) {
                sts32f(sb + OFF_ALPHA + slot * 64 + g8 * 4, a0);
                sts32f(sb + OFF_ALPHA + slot * 64 + 32 + g8 * 4, a1);
            }
            __syncwarp();
            if (lane == 0) mbar_arrive(sb + BAR_PFULL + 8 * slot);
        }
        l0 += __shfl_xor_sync(0xffffffffu, l0, 1);
        l1 += __shfl_xor_sync(0xffffffffu, l1, 1);
        l0 += __shfl_xor_sync(0xffffffffu, l0, 2);
        l1 += __shfl_xor_sync(0xffffffffu, l1, 2);
        if (quad == 0) {
            sts32f(sb + OFF_LSUM + g8 * 16 + warp * 4, l0);
            sts32f(sb + OFF_LSUM + 128 + g8 * 16 + warp * 4, l1);
            if (warp == 0) { sts32f(sb + OFF_MROW + g8 * 4, mc0); sts32f(sb + OFF_MROW + 32 + g8 * 4, mc1); }
        }
        bar_sync(2, 128);
        if (warp == 0) {
            if (lane < 16) {
                const float4 lv = lds128f(sb + OFF_LSUM + lane * 16);
                const float l = (lv.x + lv.y) + (lv.z + lv.w), m = lds32f(sb + OFF_MROW + lane * 4);
                uint32_t ra, rbar;
                asm("mapa.shared::cluster.u32 %0, %1, %2;" : "=r"(ra) : "r"(sb + OFF_STAT + (lane ^ 8) * 8), "r"(rank ^ 1));
                asm("mapa.shared::cluster.u32 %0, %1, %2;" : "=r"(rbar) : "r"(sb + BAR_STAT), "r"(rank ^ 1));
                asm volatile("st.async.weak.shared::cluster.mbarrier::complete_tx::bytes.v2.f32 [%0], {%1,%2}, [%3];"
                             ::"r"(ra), "f"(m), "f"(l), "r"(rbar) : "memory");
                mbar_wait(sb + BAR_STAT, 0);
                const float pm = lds32f(sb + OFF_STAT + lane * 8), pl = lds32f(sb + OFF_STAT + lane * 8 + 4);
                const float mm = fmaxf(m, pm);
                const float e = ex2(m - mm), pe = ex2(pm - mm);
                sts32f(sb + OFF_F + lane * 4, __fdividef(e, l * e + pl * pe));
            }
            __syncwarp();
            if (lane == 0) mbar_arrive(sb + BAR_F);
        }
        mbar_wait(sb + BAR_D, 0);
    } else {
        const int w = warp - 4;
        asm volatile("barrier.cluster.wait.acquire.aligned;" ::: "memory");
        uint4* const oo = &g_scr.o[(((bh & 7) * 4 + (lane >> 4)) * 4 + w) * 128 + (bh >> 3) * 16 + (lane & 15)];
        uint4* const oout0 = pin(oo + rank * 1024);
        uint4* const oout1 = pin(oo + (rank ^ 1) * 1024);
        const uint32_t la = pin(sb + OFF_ORECV + (w * 32 + lane) * 16), obar = pin(sb + BAR_O + 8 * w);
        uint32_t ra, rbar;
        asm volatile("mapa.shared::cluster.u32 %0, %1, %2;" : "=r"(ra) : "r"(la), "r"(rank ^ 1));
        asm volatile("mapa.shared::cluster.u32 %0, %1, %2;" : "=r"(rbar) : "r"(obar), "r"(rank ^ 1));
        float o[4][4], t[2][4][4];
#pragma unroll
        for (int j = 0; j < 16; j++) (&o[0][0])[j] = (&t[0][0][0])[j] = (&t[1][0][0])[j] = 0.f;
        const uint32_t voff = (w >> 1) * 8192 + (lane & 15) * 128;
        const int vc = (w & 1) * 4 + (lane >> 4), vx = lane & 7;
        const uint32_t v0 = pin(sb + voff + ((vc ^ vx) << 4)), v1 = pin(sb + voff + (((vc + 2) ^ vx) << 4));
        pkt_store(pout, 0, 0, 0, 0, tag ^ 1);
        pkt_store(oout0, 0, 0, 0, 0, tag ^ 1);
        uint32_t p[4][4], b0[4][4], b1[4][4];
        float a0 = 0.f, a1 = 0.f;
        auto load_v = [&](int st) {
#pragma unroll
            for (int j = 0; j < 4; j++) {
                ldsm4t(b0[j], v0 + st * STAGE + j * 2048);
                ldsm4t(b1[j], v1 + st * STAGE + j * 2048);
            }
        };
        auto next_p = [&](int i) {
            const int slot = i % NP;
            mbar_wait(sb + BAR_PFULL + 8 * slot, (i / NP) & 1);
#pragma unroll
            for (int j = 0; j < 4; j++) lds128(p[j], sb + OFF_P + slot * 2048 + j * 512 + lane * 16);
            const float n0 = lds32f(sb + OFF_ALPHA + slot * 64 + g8 * 4), n1 = lds32f(sb + OFF_ALPHA + slot * 64 + 32 + g8 * 4);
            __syncwarp();
            if (lane == 0) mbar_arrive(sb + BAR_PEMPTY + 8 * slot);
#pragma unroll
            for (int j = 0; j < 4; j++) {
                o[j][0] = fmaf(o[j][0], a0, t[0][j][0] + t[1][j][0]); o[j][1] = fmaf(o[j][1], a0, t[0][j][1] + t[1][j][1]);
                o[j][2] = fmaf(o[j][2], a1, t[0][j][2] + t[1][j][2]); o[j][3] = fmaf(o[j][3], a1, t[0][j][3] + t[1][j][3]);
            }
            a0 = n0; a1 = n1;
        };
        auto pv = [&]() {
#pragma unroll
            for (int j = 0; j < 16; j++) (&t[0][0][0])[j] = (&t[1][0][0])[j] = 0.f;
#pragma unroll
            for (int j = 0; j < 4; j++) {
                mma(t[j & 1][0], p[j], b0[j][0], b0[j][1]);
                mma(t[j & 1][1], p[j], b0[j][2], b0[j][3]);
                mma(t[j & 1][2], p[j], b1[j][0], b1[j][1]);
                mma(t[j & 1][3], p[j], b1[j][2], b1[j][3]);
            }
        };
        int st = KA + 1;
        uint32_t par = 0;
#pragma unroll 1
        for (int i = 0; i < NT - 1; i++) {
            mbar_wait(sb + BAR_FULL + 8 * st, par);
            load_v(st);
            next_p(i);
            pv();
            __syncwarp();
            if (lane == 0) mbar_arrive(sb + BAR_EMPTY + 8 * st);
            st += i < NT - KA - 1 ? 2 : 1;
            if (st >= NST) { st -= NST; par ^= 1; }
        }
        constexpr int LST = (2 * NT - 1) % NST, LPAR = ((2 * NT - 1) / NST) & 1;
        const bool landed = mbar_test(sb + BAR_FULL + 8 * LST, LPAR);
        if (landed) load_v(LST);
        next_p(NT - 1);
        mbar_wait(sb + BAR_F, 0);
        const float f0 = lds32f(sb + OFF_F + g8 * 4), f1 = lds32f(sb + OFF_F + 32 + g8 * 4);
        a0 *= f0; a1 *= f1;
#pragma unroll
        for (int j = 0; j < 4; j++) {
            o[j][0] *= a0; o[j][1] *= a0; o[j][2] *= a1; o[j][3] *= a1;
            asm volatile("" : "+f"(o[j][0]), "+f"(o[j][1]), "+f"(o[j][2]), "+f"(o[j][3]));
        }
        if (!landed) {
            mbar_wait(sb + BAR_FULL + 8 * LST, LPAR);
            load_v(LST);
        }
        auto finish = [&]() {
            pv();
#pragma unroll
            for (int j = 0; j < 4; j++) {
                o[j][0] = fmaf(t[0][j][0] + t[1][j][0], f0, o[j][0]); o[j][1] = fmaf(t[0][j][1] + t[1][j][1], f0, o[j][1]);
                o[j][2] = fmaf(t[0][j][2] + t[1][j][2], f1, o[j][2]); o[j][3] = fmaf(t[0][j][3] + t[1][j][3], f1, o[j][3]);
            }
        };
        auto send = [&]() {
#pragma unroll
            for (int k = 0; k < 4; k++) {
                const int e = k < 2 ? 2 : 0, j = (k & 1) * 2;
                asm volatile("st.async.weak.shared::cluster.mbarrier::complete_tx::bytes.v4.f32 [%0], {%1,%2,%3,%4}, [%5];"
                             ::"r"(ra + k * 2048), "f"(o[j][e]), "f"(o[j][e + 1]), "f"(o[j + 1][e]), "f"(o[j + 1][e + 1]),
                               "r"(rbar + (k < 2 ? 0 : 32)) : "memory");
            }
        };
        auto publish = [&](uint4* dst, int e, const float4& r0, const float4& r1) {
            pkt_store(dst, pack_bf16(o[0][e] + r0.x, o[0][e + 1] + r0.y), pack_bf16(o[1][e] + r0.z, o[1][e + 1] + r0.w),
                      pack_bf16(o[2][e] + r1.x, o[2][e + 1] + r1.y), pack_bf16(o[3][e] + r1.z, o[3][e + 1] + r1.w), tag);
        };
        const bool ha = mbar_test(obar, 0), hb = mbar_test(obar + 32, 0);
        if (ha && hb) {
            const float4 r0 = lds128f(la), r1 = lds128f(la + 2048), r2 = lds128f(la + 4096), r3 = lds128f(la + 6144);
            finish();
            publish(oout0, 0, r0, r1);
            publish(oout1, 2, r2, r3);
            send();
        } else {
            finish();
            send();
            mbar_wait(obar, 0);
            const float4 r0 = lds128f(la), r1 = lds128f(la + 2048);
            publish(oout0, 0, r0, r1);
        }
        if (lane == 0) mbar_arrive(sb + BAR_D);
    }

    {
        const int g = warp & 3, rh = warp >> 2;
        uint32_t a[8][2][4];
        const int kr = (lane >> 4) * 8 + (lane & 7);
        const int wc = (lane >> 3) & 1, wx = (kr >> 1) & 3;
        const uint32_t wb0 = pin(sb + OFF_WO + (g * 128 + kr) * 64 + ((wc ^ wx) << 4));
        const uint32_t wb1 = pin(sb + OFF_WO + (g * 128 + kr) * 64 + (((wc + 2) ^ wx) << 4));
        const uint32_t red = pin(sb + OFF_PRED + rh * 8192 + lane * 16);
        const uint32_t rw = pin(red + g * 512), rr = pin(red + (g & 1) * 4096 + (g >> 1) * 2048);
        const uint32_t wobar = sb + BAR_FULL + 8 * ((2 * NT) % NST + (g >> 1));
        constexpr uint32_t wopar = ((2 * NT) / NST) & 1;
        auto wo_within = [&](uint32_t clks) {
            uint32_t c0, c1;
            bool in;
            asm volatile("mov.u32 %0, %%clock;" : "=r"(c0));
            do {
                in = mbar_test(wobar, wopar);
                asm volatile("mov.u32 %0, %%clock;" : "=r"(c1));
            } while (!in && c1 - c0 < clks);
            return in;
        };
        Pkt v[8];
        const bool in0 = wo_within(O_DELAY);
        pkt_issue<8, 4, 128, 32>(v, oin);
        if (!in0) {
#pragma unroll 1
            for (int it = 0; !wo_within(O_PERIOD); it++) {
                uint32_t b[8];
#pragma unroll
                for (int i = 0; i < 8; i++) b[i] = v[i].bad(tag);
                if (it > (1 << 16)) __trap();
#pragma unroll
                for (int i = 0; i < 8; i++) pkt_reload(v[i], oin + (i >> 2) * 32 + (i & 3) * 128, b[i]);
            }
        }
#pragma unroll
        for (int ks = 0; ks < 8; ks++) {
            ldsm4t(a[ks][0], wb0 + ks * 1024);
            ldsm4t(a[ks][1], wb1 + ks * 1024);
        }
        pkt_poll<8, 4, 128, 32>(v, oin, tag | (a[7][1][3] & zero));
        float c[2][2][2][4];
#pragma unroll
        for (int j = 0; j < 32; j++) (&c[0][0][0][0])[j] = 0.f;
#pragma unroll
        for (int dq = 0; dq < 4; dq++)
#pragma unroll
            for (int t = 0; t < 2; t++) {
                mma(c[t][0][0], a[2 * dq][0], v[t * 4 + dq].w0(), v[t * 4 + dq].w1());
                mma(c[t][1][0], a[2 * dq][1], v[t * 4 + dq].w0(), v[t * 4 + dq].w1());
                mma(c[t][0][1], a[2 * dq + 1][0], v[t * 4 + dq].w2(), v[t * 4 + dq].w3());
                mma(c[t][1][1], a[2 * dq + 1][1], v[t * 4 + dq].w2(), v[t * 4 + dq].w3());
            }
#pragma unroll
        for (int t = 0; t < 2; t++)
#pragma unroll
            for (int mt = 0; mt < 2; mt++)
                sts128f(rw + t * 4096 + mt * 2048, c[t][mt][0][0] + c[t][mt][1][0], c[t][mt][0][1] + c[t][mt][1][1],
                        c[t][mt][0][2] + c[t][mt][1][2], c[t][mt][0][3] + c[t][mt][1][3]);
        bar_sync(3 + rh, 128);
        const float4 s0 = lds128f(rr), s1 = lds128f(rr + 512), s2 = lds128f(rr + 1024), s3 = lds128f(rr + 1536);
        pkt_store(pout, __float_as_uint((s0.x + s1.x) + (s2.x + s3.x)), __float_as_uint((s0.y + s1.y) + (s2.y + s3.y)),
                  __float_as_uint((s0.z + s1.z) + (s2.z + s3.z)), __float_as_uint((s0.w + s1.w) + (s2.w + s3.w)), tag);
    }

    {
        if (warp < 4) {
            Pkt v[2];
            spin(P_DELAY);
            pkt_load(v[0], pin_);
            pkt_load(v[1], pin_ + 128);
#pragma unroll 1
            for (int it = 0;; it++) {
                const uint32_t b0 = v[0].bad(tag), b1 = v[1].bad(tag);
                if (!any_bit0(or3(b0, b1, 0u))) break;
                if (it > (1 << 20)) __trap();
                pkt_reload(v[0], pin_, b0);
                pkt_reload(v[1], pin_ + 128, b1);
            }
            const float e0 = __uint_as_float(v[0].w0()) + __uint_as_float(v[1].w0()), e1 = __uint_as_float(v[0].w1()) + __uint_as_float(v[1].w1());
            const float e2 = __uint_as_float(v[0].w2()) + __uint_as_float(v[1].w2()), e3 = __uint_as_float(v[0].w3()) + __uint_as_float(v[1].w3());
            const bool hi = lane & 8, hi2 = lane & 16;
            const float k0 = (hi ? e1 : e0) + __shfl_xor_sync(0xffffffffu, hi ? e0 : e1, 8);
            const float k1 = (hi ? e3 : e2) + __shfl_xor_sync(0xffffffffu, hi ? e2 : e3, 8);
            *optr = __float2bfloat16((hi2 ? k1 : k0) + __shfl_xor_sync(0xffffffffu, hi2 ? k0 : k1, 16));
        }
        if ((cta | warp | lane) == 0)
            asm volatile("st.relaxed.gpu.global.u32 [%0], %1;" ::"l"(&g_scr.epoch), "r"(epoch + 1) : "memory");
        if (warp >= 4) mbar_wait(sb + BAR_G + 8 * (warp - 4), 0);
    }
}

__device__ float g_fq[32 * 4096], g_fo[32 * 4096];
__global__ void fb_proj(const __nv_bfloat16* a_bf, const float* a_f, const __nv_bfloat16* w, int K, int N, float* o_f,
                        __nv_bfloat16* o_bf) {
    const int c = blockIdx.x * blockDim.x + threadIdx.x, r = blockIdx.y;
    float s = 0.f;
    for (int k = 0; k < K; k++) s += (a_bf ? __bfloat162float(a_bf[r * K + k]) : a_f[r * K + k]) * __bfloat162float(w[k * N + c]);
    if (o_bf) o_bf[r * N + c] = __float2bfloat16(s);
    else o_f[r * N + c] = __bfloat162float(__float2bfloat16(s));
}
__global__ void fb_attn(const __nv_bfloat16* kc, const __nv_bfloat16* vc) {
    __shared__ float sc[2048], red[128];
    const int r = blockIdx.x, hq = blockIdx.y, t = threadIdx.x;
    const size_t base = (size_t)((r >> 2) * 8 + (hq >> 2)) * 2048 * 128;
    float m = -INFINITY, l = 0.f, acc = 0.f;
    for (int j = t; j < 2048; j += 128) {
        float s = 0.f;
        for (int d = 0; d < 128; d++) s += g_fq[r * 4096 + hq * 128 + d] * __bfloat162float(kc[base + j * 128 + d]);
        sc[j] = s * 0.08838834764831845f;
        m = fmaxf(m, sc[j]);
    }
    red[t] = m;
    __syncthreads();
    for (int i = 0; i < 128; i++) m = fmaxf(m, red[i]);
    for (int j = t; j < 2048; j += 128) sc[j] = __expf(sc[j] - m);
    __syncthreads();
    for (int j = 0; j < 2048; j++) {
        l += sc[j];
        acc += sc[j] * __bfloat162float(vc[base + j * 128 + t]);
    }
    g_fo[r * 4096 + hq * 128 + t] = __bfloat162float(__float2bfloat16(acc / l));
}

typedef CUresult (*EncodeFn)(CUtensorMap*, CUtensorMapDataType, cuuint32_t, void*, const cuuint64_t*, const cuuint64_t*,
                             const cuuint32_t*, const cuuint32_t*, CUtensorMapInterleave, CUtensorMapSwizzle,
                             CUtensorMapL2promotion, CUtensorMapFloatOOBfill);

static void encode(EncodeFn fn, CUtensorMap* m, void* p, int rank, const cuuint64_t* dims, const cuuint64_t* strides,
                   const cuuint32_t* box, CUtensorMapSwizzle sw) {
    const cuuint32_t es[3] = {1, 1, 1};
    fn(m, CU_TENSOR_MAP_DATA_TYPE_BFLOAT16, rank, p, dims, strides, box, es, CU_TENSOR_MAP_INTERLEAVE_NONE, sw,
       CU_TENSOR_MAP_L2_PROMOTION_L2_256B, CU_TENSOR_MAP_FLOAT_OOB_FILL_NONE);
}

}

extern "C" void kernel_launch(void* const* d_in, const int* in_sizes, int n_in, void* d_out, int out_size) {
    using namespace gqa;
    static EncodeFn fn = nullptr;
    static uint32_t slot_ns = SLOT_NS;
    static bool fits = false;
    if (!fn) {
        int dev = 0, khz = 0, bits = 0;
        cudaGetDevice(&dev);
        cudaDeviceGetAttribute(&khz, cudaDevAttrMemoryClockRate, dev);
        cudaDeviceGetAttribute(&bits, cudaDevAttrGlobalMemoryBusWidth, dev);
        if (khz > 0 && bits > 0) slot_ns = (uint32_t)((double)NCTA * STAGE / (0.955 * 2.0 * khz * 1e-6 * (bits / 8)));
        void* p = nullptr;
        cudaDriverEntryPointQueryResult qr;
        cudaGetDriverEntryPoint("cuTensorMapEncodeTiled", &p, cudaEnableDefault, &qr);
        fn = (EncodeFn)p;
        cudaFuncSetAttribute(gqa_kernel, cudaFuncAttributeMaxDynamicSharedMemorySize, SMEM_BYTES);
        cudaLaunchConfig_t cfg = {};
        cfg.gridDim = dim3(NCTA);
        cfg.blockDim = dim3(288);
        cfg.dynamicSmemBytes = SMEM_BYTES;
        int clusters = 0;
        fits = cudaOccupancyMaxActiveClusters(&clusters, gqa_kernel, &cfg) == cudaSuccess && clusters >= NCTA / 2;
    }
    if (!fits) {
        float *fq = nullptr, *fo = nullptr;
        cudaGetSymbolAddress((void**)&fq, g_fq);
        cudaGetSymbolAddress((void**)&fo, g_fo);
        fb_proj<<<dim3(16, 32), 256, 0, cudaStreamPerThread>>>((const __nv_bfloat16*)d_in[0], nullptr, (const __nv_bfloat16*)d_in[3], 512,
                                                               4096, fq, nullptr);
        fb_attn<<<dim3(32, 32), 128, 0, cudaStreamPerThread>>>((const __nv_bfloat16*)d_in[1], (const __nv_bfloat16*)d_in[2]);
        fb_proj<<<dim3(2, 32), 256, 0, cudaStreamPerThread>>>(nullptr, fo, (const __nv_bfloat16*)d_in[4], 4096, 512, nullptr,
                                                              (__nv_bfloat16*)d_out);
        return;
    }
    CUtensorMap tmK, tmV, tmX, tmWq, tmWo;
    {
        const cuuint64_t dims[3] = {64, 8 * 8 * 2048, 2}, str[2] = {256, 128};
        const cuuint32_t box[3] = {64, 64, 2};
        encode(fn, &tmK, d_in[1], 3, dims, str, box, CU_TENSOR_MAP_SWIZZLE_128B);
        encode(fn, &tmV, d_in[2], 3, dims, str, box, CU_TENSOR_MAP_SWIZZLE_128B);
    }
    {
        const cuuint64_t dims[3] = {64, 32, 8}, str[2] = {1024, 128};
        const cuuint32_t box[3] = {64, 32, 8};
        encode(fn, &tmX, d_in[0], 3, dims, str, box, CU_TENSOR_MAP_SWIZZLE_128B);
    }
    {
        const cuuint64_t dq[2] = {4096, 512}, sq[1] = {8192}, dw[2] = {512, 4096}, sw[1] = {1024};
        const cuuint32_t box[2] = {32, 256};
        encode(fn, &tmWq, d_in[3], 2, dq, sq, box, CU_TENSOR_MAP_SWIZZLE_64B);
        encode(fn, &tmWo, d_in[4], 2, dw, sw, box, CU_TENSOR_MAP_SWIZZLE_64B);
    }
    gqa_kernel<<<NCTA, 288, SMEM_BYTES, cudaStreamPerThread>>>(Ptrs{{(const uint8_t*)d_in[3], nullptr}}, (__nv_bfloat16*)d_out, slot_ns, 0u, tmK, tmV, tmX,
                                                               tmWq, tmWo);
}
```

```cpp
#include <cuda_runtime.h>
#include <cuda_bf16.h>
#include <cuda.h>
#include <stdint.h>

namespace gqa {

constexpr int PA_NS = 2320;
constexpr int SLOT_NS = 655;
constexpr int WO_SLOT = 2980;
constexpr int WO_STEP = 60;
constexpr int Q_DELAY_NS = 1000;
constexpr int O_DELAY = 900;
constexpr int O_PERIOD = 800;
constexpr int P_DELAY = 330;
constexpr int PF_BYTES = 8192;

constexpr int NCTA = 128;
constexpr int NT = 16;
constexpr int NST = 13;
constexpr int NST0 = 10;
constexpr int WIN0 = 3;
constexpr int WIN = 6;
constexpr int WSW = 8;
constexpr int KA = 2;
constexpr int NP = 4;
constexpr int STAGE = 16384;

constexpr int OFF_WQ = NST0 * STAGE;
constexpr int OFF_X = OFF_WQ + 32768;
constexpr int OFF_QRED = OFF_X;
constexpr int OFF_WO = ((2 * NT) % NST) * STAGE;
constexpr int OFF_P = NST * STAGE;
constexpr int OFF_ORECV = (((2 * NT) % NST) + 3) * STAGE;
constexpr int OFF_ALPHA = OFF_P + NP * 2048;
constexpr int OFF_WMAX = OFF_ALPHA + NP * 64;
constexpr int OFF_LSUM = OFF_WMAX + 512;
constexpr int OFF_MROW = OFF_LSUM + 256;
constexpr int OFF_STAT = OFF_MROW + 64;
constexpr int OFF_F = OFF_STAT + 128;
constexpr int OFF_PRED = (((2 * NT) % NST) + 2) * STAGE;
constexpr int OFF_BAR = (NST + 1) * STAGE;
constexpr int BAR_FULL = OFF_BAR;
constexpr int BAR_EMPTY = BAR_FULL + 8 * NST;
constexpr int BAR_PFULL = BAR_EMPTY + 8 * NST;
constexpr int BAR_PEMPTY = BAR_PFULL + 8 * NP;
constexpr int BAR_W = BAR_PEMPTY + 8 * NP;
constexpr int BAR_STAT = BAR_W + 8;
constexpr int BAR_F = BAR_STAT + 8;
constexpr int BAR_O = BAR_F + 8;
constexpr int BAR_G = BAR_O + 32;
constexpr int BAR_D = BAR_G + 32;
constexpr int BAR_WO = BAR_D + 8;
constexpr int SMEM_BYTES = OFF_BAR + 512;
static_assert(OFF_F + 64 <= OFF_BAR, "scratch overflows its slot");
static_assert(BAR_WO + 32 <= SMEM_BYTES, "barriers overflow");
static_assert((2 * NT) % NST + 3 < NST, "wo / partial slots must not wrap");
static_assert(SMEM_BYTES <= 232448, "too much shared memory");

struct Scratch {
    uint4 q[32 * 4 * 8 * 16];
    uint4 o[32 * 4 * 8 * 16];
    uint4 p[128 * 8 * 32];
    unsigned epoch;
};
__device__ Scratch g_scr;

__device__ __forceinline__ void mbar_init(uint32_t bar, uint32_t cnt) {
    asm volatile("mbarrier.init.shared::cta.b64 [%0], %1;" ::"r"(bar), "r"(cnt) : "memory");
}
__device__ __forceinline__ void mbar_expect_tx(uint32_t bar, uint32_t bytes) {
    asm volatile("mbarrier.arrive.expect_tx.shared::cta.b64 _, [%0], %1;" ::"r"(bar), "r"(bytes) : "memory");
}
__device__ __forceinline__ void mbar_arrive(uint32_t bar) {
    asm volatile("mbarrier.arrive.shared::cta.b64 _, [%0];" ::"r"(bar) : "memory");
}
__device__ __forceinline__ bool mbar_try(uint32_t bar, uint32_t parity) {
    uint32_t ok;
    asm volatile("{\n.reg .pred p;\nmbarrier.try_wait.parity.shared::cta.b64 p, [%1], %2;\nselp.u32 %0, 1, 0, p;\n}"
                 : "=r"(ok) : "r"(bar), "r"(parity) : "memory");
    return ok;
}
__device__ __forceinline__ bool mbar_test(uint32_t bar, uint32_t parity) {
    uint32_t ok;
    asm volatile("{\n.reg .pred p;\nmbarrier.test_wait.parity.shared::cta.b64 p, [%1], %2;\nselp.u32 %0, 1, 0, p;\n}"
                 : "=r"(ok) : "r"(bar), "r"(parity) : "memory");
    return ok;
}
__device__ __forceinline__ void mbar_wait(uint32_t bar, uint32_t parity) {
#pragma unroll 1
    for (int i = 0; !mbar_try(bar, parity); i++)
        if (i > (1 << 20)) __trap();
}
__device__ __forceinline__ void tma2d(uint32_t dst, const CUtensorMap* m, int c0, int c1, uint32_t bar) {
    asm volatile("cp.async.bulk.tensor.2d.shared::cluster.global.mbarrier::complete_tx::bytes [%0], [%1, {%3, %4}], [%2];"
                 ::"r"(dst), "l"(m), "r"(bar), "r"(c0), "r"(c1) : "memory");
}
__device__ __forceinline__ void tma3d(uint32_t dst, const CUtensorMap* m, int c0, int c1, int c2, uint32_t bar) {
    asm volatile("cp.async.bulk.tensor.3d.shared::cluster.global.mbarrier::complete_tx::bytes [%0], [%1, {%3, %4, %5}], [%2];"
                 ::"r"(dst), "l"(m), "r"(bar), "r"(c0), "r"(c1), "r"(c2) : "memory");
}
__device__ __forceinline__ void tma3d_hint(uint32_t dst, const CUtensorMap* m, int c0, int c1, int c2, uint32_t bar, uint64_t pol) {
    asm volatile("cp.async.bulk.tensor.3d.shared::cluster.global.mbarrier::complete_tx::bytes.L2::cache_hint [%0], [%1, {%3, %4, %5}], [%2], %6;"
                 ::"r"(dst), "l"(m), "r"(bar), "r"(c0), "r"(c1), "r"(c2), "l"(pol) : "memory");
}
__device__ __forceinline__ void ldsm4(uint32_t (&r)[4], uint32_t addr) {
    asm volatile("ldmatrix.sync.aligned.m8n8.x4.shared.b16 {%0,%1,%2,%3}, [%4];"
                 : "=r"(r[0]), "=r"(r[1]), "=r"(r[2]), "=r"(r[3]) : "r"(addr) : "memory");
}
__device__ __forceinline__ void ldsm4t(uint32_t (&r)[4], uint32_t addr) {
    asm volatile("ldmatrix.sync.aligned.m8n8.x4.trans.shared.b16 {%0,%1,%2,%3}, [%4];"
                 : "=r"(r[0]), "=r"(r[1]), "=r"(r[2]), "=r"(r[3]) : "r"(addr) : "memory");
}
__device__ __forceinline__ void mma(float (&c)[4], const uint32_t (&a)[4], uint32_t b0, uint32_t b1) {
    asm volatile("mma.sync.aligned.m16n8k16.row.col.f32.bf16.bf16.f32 {%0,%1,%2,%3}, {%4,%5,%6,%7}, {%8,%9}, {%0,%1,%2,%3};"
                 : "+f"(c[0]), "+f"(c[1]), "+f"(c[2]), "+f"(c[3])
                 : "r"(a[0]), "r"(a[1]), "r"(a[2]), "r"(a[3]), "r"(b0), "r"(b1));
}
__device__ __forceinline__ uint32_t pack_bf16(float lo, float hi) {
    uint32_t r;
    asm("cvt.rn.bf16x2.f32 %0, %1, %2;" : "=r"(r) : "f"(hi), "f"(lo));
    return r;
}
__device__ __forceinline__ float ex2(float x) {
    float y;
    asm("ex2.approx.ftz.f32 %0, %1;" : "=f"(y) : "f"(x));
    return y;
}
__device__ __forceinline__ void sts128(uint32_t addr, uint32_t a, uint32_t b, uint32_t c, uint32_t d) {
    asm volatile("st.shared.v4.b32 [%0], {%1,%2,%3,%4};" ::"r"(addr), "r"(a), "r"(b), "r"(c), "r"(d) : "memory");
}
__device__ __forceinline__ void sts128f(uint32_t addr, float a, float b, float c, float d) {
    asm volatile("st.shared.v4.f32 [%0], {%1,%2,%3,%4};" ::"r"(addr), "f"(a), "f"(b), "f"(c), "f"(d) : "memory");
}
__device__ __forceinline__ void sts32f(uint32_t addr, float a) {
    asm volatile("st.shared.f32 [%0], %1;" ::"r"(addr), "f"(a) : "memory");
}
__device__ __forceinline__ void lds128(uint32_t (&r)[4], uint32_t addr) {
    asm volatile("ld.shared.v4.b32 {%0,%1,%2,%3}, [%4];" : "=r"(r[0]), "=r"(r[1]), "=r"(r[2]), "=r"(r[3]) : "r"(addr) : "memory");
}
__device__ __forceinline__ float4 lds128f(uint32_t addr) {
    float4 v;
    asm volatile("ld.shared.v4.f32 {%0,%1,%2,%3}, [%4];" : "=f"(v.x), "=f"(v.y), "=f"(v.z), "=f"(v.w) : "r"(addr) : "memory");
    return v;
}
__device__ __forceinline__ float lds32f(uint32_t addr) {
    float v;
    asm volatile("ld.shared.f32 %0, [%1];" : "=f"(v) : "r"(addr) : "memory");
    return v;
}
__device__ __forceinline__ void bar_sync(int id, int n) { asm volatile("bar.sync %0, %1;" ::"r"(id), "r"(n) : "memory"); }
template <typename T> __device__ __forceinline__ T* pin(T* p) { asm volatile("" : "+l"(p)); return p; }
__device__ __forceinline__ uint32_t pin(uint32_t v) { asm volatile("" : "+r"(v)); return v; }

struct Pkt {
    uint64_t lo, hi;
    __device__ __forceinline__ uint32_t w0() const { return (uint32_t)lo; }
    __device__ __forceinline__ uint32_t w1() const { return (uint32_t)(lo >> 32); }
    __device__ __forceinline__ uint32_t w2() const { return (uint32_t)hi; }
    __device__ __forceinline__ uint32_t w3() const { return (uint32_t)(hi >> 32); }
    __device__ __forceinline__ uint32_t bad(uint32_t tag) const {
        uint32_t r;
        asm("lop3.b32 %0, %1, %2, %3, 0x7E;" : "=r"(r) : "r"(w0()), "r"(w2()), "r"(tag));
        return r;
    }
};
__device__ __forceinline__ void pkt_store(uint4* p, uint32_t a, uint32_t b, uint32_t c, uint32_t d, uint32_t tag) {
    a = (a & ~1u) | tag;
    c = (c & ~1u) | tag;
    asm volatile("{\n.reg .b64 lo, hi;\nmov.b64 lo, {%1,%2};\nmov.b64 hi, {%3,%4};\n"
                 "st.relaxed.gpu.global.v2.b64 [%0], {lo, hi};\n}" ::"l"(p), "r"(a), "r"(b), "r"(c), "r"(d) : "memory");
}
__device__ __forceinline__ void pkt_load(Pkt& v, const uint4* p) {
    asm volatile("ld.relaxed.gpu.global.v2.b64 {%0, %1}, [%2];" : "=l"(v.lo), "=l"(v.hi) : "l"(p) : "memory");
}
__device__ __forceinline__ void pkt_reload(Pkt& v, const uint4* p, uint32_t bad) {
    asm volatile("{\n.reg .pred p;\n.reg .b32 t;\nand.b32 t, %3, 1;\nsetp.ne.u32 p, t, 0;\n"
                 "@p ld.relaxed.gpu.global.v2.b64 {%0, %1}, [%2];\n}"
                 : "+l"(v.lo), "+l"(v.hi) : "l"(p), "r"(bad) : "memory");
}
__device__ __forceinline__ uint32_t or3(uint32_t a, uint32_t b, uint32_t c) {
    uint32_t r;
    asm("lop3.b32 %0, %1, %2, %3, 0xFE;" : "=r"(r) : "r"(a), "r"(b), "r"(c));
    return r;
}
__device__ __forceinline__ bool any_bit0(uint32_t x) {
    uint32_t r;
    asm volatile("{\n.reg .pred p, q;\n.reg .b32 t;\nand.b32 t, %1, 1;\nsetp.ne.u32 p, t, 0;\nvote.sync.any.pred q, p, 0xffffffff;\n"
                 "selp.u32 %0, 1, 0, q;\n}" : "=r"(r) : "r"(x));
    return r;
}
template <int N, int N0, int S0, int S1>
__device__ __forceinline__ void pkt_issue(Pkt (&v)[N], const uint4* p) {
#pragma unroll
    for (int i = 0; i < N; i++) pkt_load(v[i], p + (i / N0) * S1 + (i % N0) * S0);
}
template <int N, int N0, int S0, int S1>
__device__ __forceinline__ void pkt_poll(Pkt (&v)[N], const uint4* p, uint32_t tag) {
    static_assert(N == 1 || N == 8, "");
#pragma unroll 1
    for (int it = 0;; it++) {
        uint32_t b[N];
#pragma unroll
        for (int i = 0; i < N; i++) b[i] = v[i].bad(tag);
        uint32_t bad = b[0];
        if (N == 8) bad = or3(or3(b[0], b[1 % N], b[2 % N]), or3(b[3 % N], b[4 % N], b[5 % N]), or3(b[6 % N], b[7 % N], 0u));
        if (!any_bit0(bad)) break;
#pragma unroll
        for (int i = 0; i < N; i++) pkt_reload(v[i], p + (i / N0) * S1 + (i % N0) * S0, b[i]);
        if (it > (1 << 20)) __trap();
    }
}

__device__ __forceinline__ uint32_t now_ns() {
    uint32_t t;
    asm volatile("mov.u32 %0, %%globaltimer_lo;" : "=r"(t));
    return t;
}
__device__ __forceinline__ void spin(uint32_t clks) {
    uint32_t c0, c1;
    asm volatile("mov.u32 %0, %%clock;" : "=r"(c0));
    do { asm volatile("mov.u32 %0, %%clock;" : "=r"(c1)); } while (c1 - c0 < clks);
}
__device__ __forceinline__ void wait_until(uint32_t t) {
#pragma unroll 1
    for (int i = 0; (int)(now_ns() - t) < 0 && i < (1 << 16); i++) {}
}

struct Ptrs { const uint8_t* p[2]; };

__global__ void __cluster_dims__(2, 1, 1) __launch_bounds__(288, 1)
gqa_kernel(const __grid_constant__ Ptrs ptrs, __nv_bfloat16* __restrict__ out, uint32_t slot_ns, uint32_t zero,
           const __grid_constant__ CUtensorMap tmK, const __grid_constant__ CUtensorMap tmV,
           const __grid_constant__ CUtensorMap tmX, const __grid_constant__ CUtensorMap tmWq,
           const __grid_constant__ CUtensorMap tmWo) {
    const uint32_t tstart = now_ns();
    if (threadIdx.x == 32)
        asm volatile("cp.async.bulk.prefetch.L2.global [%0], %1;" ::"l"(ptrs.p[blockIdx.x >> 10] + blockIdx.x * PF_BYTES), "r"(PF_BYTES)
                     : "memory");
    extern __shared__ __align__(1024) uint8_t smem_raw[];
    const uint32_t sb = pin((uint32_t)__cvta_generic_to_shared(smem_raw));
    if (threadIdx.x == 0) {
        mbar_init(sb + BAR_W, 1);
        asm volatile("fence.mbarrier_init.release.cluster;" ::: "memory");
        mbar_expect_tx(sb + BAR_W, 65536);
        tma2d(sb + OFF_WQ, &tmWq, blockIdx.x * 32, 0, sb + BAR_W);
        tma2d(sb + OFF_WQ + 16384, &tmWq, blockIdx.x * 32, 256, sb + BAR_W);
        tma3d(sb + OFF_X, &tmX, 0, 0, 0, sb + BAR_W);
    }
    const int warp = __shfl_sync(0xffffffffu, threadIdx.x >> 5, 0), lane = pin(threadIdx.x & 31);
    const int cta = pin(blockIdx.x), rank = cta & 1, bh = cta >> 1;

    if (warp == 8) {
        const int row0 = bh * 2048 + rank * 64;
        uint64_t pol;
        asm volatile("createpolicy.fractional.L2::evict_first.b64 %0, 1.0;" : "=l"(pol));
        auto issue = [&](int n) {
            const bool isv = n >= 2 * NT - KA || (n >= KA && ((n - KA) & 1));
            const int t = n < KA ? n : n >= 2 * NT - KA ? n - NT : isv ? (n - KA) >> 1 : (n + KA) >> 1;
            const int st = n % NST;
            tma3d_hint(sb + st * STAGE, isv ? &tmV : &tmK, 0, row0 + t * 128, 0, sb + BAR_FULL + 8 * st, pol);
        };
        if (lane == 0) {
            if (sb & 1023) __trap();
#pragma unroll
            for (int i = 0; i < WIN0; i++) mbar_init(sb + BAR_FULL + 8 * i, 1);
            asm volatile("fence.mbarrier_init.release.cluster;" ::: "memory");
#pragma unroll
            for (int n = 0; n < WIN0; n++) {
                mbar_expect_tx(sb + BAR_FULL + 8 * n, STAGE);
                issue(n);
            }
            for (int i = WIN0; i < NST; i++) mbar_init(sb + BAR_FULL + 8 * i, 1);
            for (int i = 0; i < NST; i++) mbar_init(sb + BAR_EMPTY + 8 * i, 4);
            for (int i = 0; i < NP; i++) {
                mbar_init(sb + BAR_PFULL + 8 * i, 4);
                mbar_init(sb + BAR_PEMPTY + 8 * i, 4);
            }
            mbar_init(sb + BAR_STAT, 1);
            mbar_init(sb + BAR_F, 1);
            mbar_init(sb + BAR_D, 4);
            mbar_expect_tx(sb + BAR_STAT, 128);
            for (int i = 0; i < 4; i++) {
                mbar_init(sb + BAR_O + 8 * i, 1);
                mbar_expect_tx(sb + BAR_O + 8 * i, 1024);
                mbar_init(sb + BAR_G + 8 * i, 1);
                mbar_expect_tx(sb + BAR_G + 8 * i, 1024);
                mbar_init(sb + BAR_WO + 8 * i, 1);
                mbar_expect_tx(sb + BAR_WO + 8 * i, 8192);
            }
            asm volatile("fence.mbarrier_init.release.cluster;" ::: "memory");
            asm volatile("prefetch.tensormap [%0];" ::"l"(&tmWo) : "memory");
        }
        __syncthreads();
        asm volatile("barrier.cluster.arrive.relaxed.aligned;" ::: "memory");
        if (lane == 0) {
            auto wait_free = [&](int n) {
                const int st = n % NST, k = n / NST;
                if (st >= NST0) mbar_wait(sb + BAR_EMPTY + 8 * st, k & 1);
                else if (k) mbar_wait(sb + BAR_EMPTY + 8 * st, (k - 1) & 1);
            };
            const uint32_t t3 = tstart + PA_NS;
#pragma unroll
            for (int n = WIN0; n < 2 * NT; n++) {
                wait_free(n);
                mbar_expect_tx(sb + BAR_FULL + 8 * (n % NST), STAGE);
                if (n < WSW || n >= WSW + WIN - WIN0) {
                    const int d = n - (n < WSW ? WIN0 : WIN);
                    mbar_wait(sb + BAR_FULL + 8 * (d % NST), (d / NST) & 1);
                }
                if (n >= WSW) wait_until(t3 + (n - 3) * slot_ns);
                issue(n);
            }
            wait_free(2 * NT); wait_free(2 * NT + 1); wait_free(2 * NT + 2);
#pragma unroll
            for (int g = 0; g < 4; g++) {
                wait_until(t3 + (WO_SLOT + g * WO_STEP) * slot_ns / 100);
                tma2d(sb + OFF_WO + g * 8192, &tmWo, (cta & 15) * 32, (cta >> 4) * 512 + g * 128, sb + BAR_WO + 8 * g);
            }
        }
        return;
    }

    unsigned epoch;
    asm volatile("ld.relaxed.gpu.global.u32 %0, [%1];" : "=r"(epoch) : "l"(&g_scr.epoch) : "memory");
    const int g8 = lane >> 2, quad = lane & 3;
    const int rh = warp >> 2, g = (warp + 2 * rh) & 3;
    const uint4* const oin = pin(&g_scr.o[((cta >> 4) * 4 + g) * 512 + rh * 64 + lane]);
    uint4* const pout = pin(&g_scr.p[(((rh * 2 + (g & 1)) * 32 + (cta & 15) * 2 + (g >> 1)) * 8 + (cta >> 4)) * 32 + quad * 8 + g8]);
    const uint4* const pin_ = pin(&g_scr.p[(cta * 8 + (lane >> 3)) * 32 + (warp & 3) * 8 + (lane & 7)]);
    __nv_bfloat16* const optr = pin(out + ((cta >> 5) * 8 + (warp & 3) * 2 + ((lane >> 3) & 1)) * 512 + (cta & 31) * 16 + (lane & 7) +
                                    (lane >> 4) * 8);
    __syncthreads();

    {
        const int kq = warp & 3, mt = warp >> 2;
        float c[4][4];
#pragma unroll
        for (int j = 0; j < 4; j++) c[j][0] = c[j][1] = c[j][2] = c[j][3] = 0.f;
        const int ar = mt * 16 + (lane & 15);
        const uint32_t abase = sb + OFF_X + kq * 8192 + ar * 128;
        const int br = lane & 15;
        const uint32_t bbase = sb + OFF_WQ + (kq * 128 + br) * 64;
        if (warp < 4) pkt_store(&g_scr.q[cta * 128 + warp * 32 + lane], 0, 0, 0, 0, epoch & 1);
        pkt_store(pout, 0, 0, 0, 0, epoch & 1);
        mbar_wait(sb + BAR_W, 0);
#pragma unroll
        for (int ks = 0; ks < 8; ks++) {
            uint32_t a[4], b0[4], b1[4];
            ldsm4(a, abase + (ks >> 2) * 4096 + ((((ks & 3) * 2 + (lane >> 4)) ^ (ar & 7)) << 4));
            ldsm4t(b0, bbase + ks * 1024 + (((lane >> 4) ^ ((br >> 1) & 3)) << 4));
            ldsm4t(b1, bbase + ks * 1024 + (((2 + (lane >> 4)) ^ ((br >> 1) & 3)) << 4));
            mma(c[0], a, b0[0], b0[1]);
            mma(c[1], a, b0[2], b0[3]);
            mma(c[2], a, b1[0], b1[1]);
            mma(c[3], a, b1[2], b1[3]);
        }
        bar_sync(1, 256);
        asm volatile("barrier.cluster.arrive.relaxed.aligned;" ::: "memory");
        const uint32_t rb = sb + OFF_QRED + (kq * 2 + mt) * 2048 + lane * 16;
        sts128f(rb, c[0][0], c[0][1], c[1][0], c[1][1]);
        sts128f(rb + 512, c[2][0], c[2][1], c[3][0], c[3][1]);
        sts128f(rb + 1024, c[0][2], c[0][3], c[1][2], c[1][3]);
        sts128f(rb + 1536, c[2][2], c[2][3], c[3][2], c[3][3]);
        bar_sync(1, 256);
    }
    const uint32_t tag = pin((epoch + 1) & 1);

    if (warp < 4) {
        {
            const uint32_t rb = sb + OFF_QRED + warp * 1024 + lane * 16;
            float4 s0 = lds128f(rb), s1 = lds128f(rb + 512);
#pragma unroll
            for (int kq = 1; kq < 4; kq++) {
                float4 t0 = lds128f(rb + kq * 4096), t1 = lds128f(rb + kq * 4096 + 512);
                s0.x += t0.x; s0.y += t0.y; s0.z += t0.z; s0.w += t0.w;
                s1.x += t1.x; s1.y += t1.y; s1.z += t1.z; s1.w += t1.w;
            }
            pkt_store(&g_scr.q[cta * 128 + warp * 32 + lane], pack_bf16(s0.x, s0.y), pack_bf16(s0.z, s0.w),
                      pack_bf16(s1.x, s1.y), pack_bf16(s1.z, s1.w), tag);
            __syncwarp();
            if (lane < NST - NST0) mbar_arrive(sb + BAR_EMPTY + 8 * (NST0 + lane));
        }
        __nanosleep(Q_DELAY_NS);
        uint32_t q[8][4];
        {
            Pkt v[8];
            const uint4* qp = &g_scr.q[(((bh & 7) * 4 + (lane >> 4)) * 4) * 128 + (bh >> 3) * 16 + (lane & 15)];
            pkt_issue<8, 4, 128, 1024>(v, qp);
            pkt_poll<8, 4, 128, 1024>(v, qp, tag);
#pragma unroll
            for (int dq = 0; dq < 4; dq++) {
                const Pkt a = rank ? v[4 + dq] : v[dq], b = rank ? v[dq] : v[4 + dq];
                q[2 * dq][0] = a.w0();     q[2 * dq][1] = b.w0();     q[2 * dq][2] = a.w1();     q[2 * dq][3] = b.w1();
                q[2 * dq + 1][0] = a.w2(); q[2 * dq + 1][1] = b.w2(); q[2 * dq + 1][2] = a.w3(); q[2 * dq + 1][3] = b.w3();
            }
        }
        asm volatile("barrier.cluster.wait.acquire.aligned;" ::: "memory");
        constexpr float C = 0.08838834764831845f * 1.4426950408889634f;
        float mc0 = -INFINITY, mc1 = -INFINITY, l0 = 0.f, l1 = 0.f;
        const int key = warp * 16 + (lane >> 4) * 8 + (lane & 7);
        const uint32_t koff = key * 128;
        const int ksel = (lane >> 3) & 1, kx = lane & 7;
        int st = 0;
        uint32_t par = 0;
#pragma unroll 1
        for (int i = 0; i < NT; i++) {
            const uint32_t kb = sb + st * STAGE + koff;
            float s[2][2][4];
#pragma unroll
            for (int j = 0; j < 4; j++) s[0][0][j] = s[0][1][j] = s[1][0][j] = s[1][1][j] = 0.f;
            mbar_wait(sb + BAR_FULL + 8 * st, par);
#pragma unroll
            for (int ks = 0; ks < 8; ks++) {
                uint32_t b[4];
                ldsm4(b, kb + (ks >> 2) * 8192 + ((((ks & 3) * 2 + ksel) ^ kx) << 4));
                mma(s[ks & 1][0], q[ks], b[0], b[1]);
                mma(s[ks & 1][1], q[ks], b[2], b[3]);
            }
            __syncwarp();
            if (lane == 0) mbar_arrive(sb + BAR_EMPTY + 8 * st);
            st += i < KA ? 1 : 2;
            if (st >= NST) { st -= NST; par ^= 1; }
            float sv[2][4];
#pragma unroll
            for (int j = 0; j < 4; j++) { sv[0][j] = s[0][0][j] + s[1][0][j]; sv[1][j] = s[0][1][j] + s[1][1][j]; }
            float t0 = fmaxf(fmaxf(sv[0][0], sv[0][1]), fmaxf(sv[1][0], sv[1][1]));
            float t1 = fmaxf(fmaxf(sv[0][2], sv[0][3]), fmaxf(sv[1][2], sv[1][3]));
            t0 = fmaxf(t0, __shfl_xor_sync(0xffffffffu, t0, 1));
            t1 = fmaxf(t1, __shfl_xor_sync(0xffffffffu, t1, 1));
            t0 = fmaxf(t0, __shfl_xor_sync(0xffffffffu, t0, 2));
            t1 = fmaxf(t1, __shfl_xor_sync(0xffffffffu, t1, 2));
            const uint32_t wm = sb + OFF_WMAX + (i & 1) * 256 + g8 * 16;
            if (quad == 0) { sts32f(wm + warp * 4, t0); sts32f(wm + 128 + warp * 4, t1); }
            bar_sync(2, 128);
            const float4 w0 = lds128f(wm), w1 = lds128f(wm + 128);
            const float n0 = fmaxf(mc0, fmaxf(fmaxf(w0.x, w0.y), fmaxf(w0.z, w0.w)) * C);
            const float n1 = fmaxf(mc1, fmaxf(fmaxf(w1.x, w1.y), fmaxf(w1.z, w1.w)) * C);
            const float a0 = ex2(mc0 - n0), a1 = ex2(mc1 - n1);
            mc0 = n0; mc1 = n1;
            float p[2][4];
#pragma unroll
            for (int j = 0; j < 2; j++) {
                p[j][0] = ex2(fmaf(sv[j][0], C, -n0)); p[j][1] = ex2(fmaf(sv[j][1], C, -n0));
                p[j][2] = ex2(fmaf(sv[j][2], C, -n1)); p[j][3] = ex2(fmaf(sv[j][3], C, -n1));
            }
            l0 = l0 * a0 + ((p[0][0] + p[0][1]) + (p[1][0] + p[1][1]));
            l1 = l1 * a1 + ((p[0][2] + p[0][3]) + (p[1][2] + p[1][3]));
            const int slot = i % NP;
            if (i >= NP) mbar_wait(sb + BAR_PEMPTY + 8 * slot, (i / NP - 1) & 1);
            sts128(sb + OFF_P + slot * 2048 + warp * 512 + lane * 16, pack_bf16(p[0][0], p[0][1]), pack_bf16(p[0][2], p[0][3]),
                   pack_bf16(p[1][0], p[1][1]), pack_bf16(p[1][2], p[1][3]));
            if (warp == 0 && quad == 0) {
                sts32f(sb + OFF_ALPHA + slot * 64 + g8 * 4, a0);
                sts32f(sb + OFF_ALPHA + slot * 64 + 32 + g8 * 4, a1);
            }
            __syncwarp();
            if (lane == 0) mbar_arrive(sb + BAR_PFULL + 8 * slot);
        }
        l0 += __shfl_xor_sync(0xffffffffu, l0, 1);
        l1 += __shfl_xor_sync(0xffffffffu, l1, 1);
        l0 += __shfl_xor_sync(0xffffffffu, l0, 2);
        l1 += __shfl_xor_sync(0xffffffffu, l1, 2);
        if (quad == 0) {
            sts32f(sb + OFF_LSUM + g8 * 16 + warp * 4, l0);
            sts32f(sb + OFF_LSUM + 128 + g8 * 16 + warp * 4, l1);
            if (warp == 0) { sts32f(sb + OFF_MROW + g8 * 4, mc0); sts32f(sb + OFF_MROW + 32 + g8 * 4, mc1); }
        }
        bar_sync(2, 128);
        if (warp == 0) {
            if (lane < 16) {
                const float4 lv = lds128f(sb + OFF_LSUM + lane * 16);
                const float l = (lv.x + lv.y) + (lv.z + lv.w), m = lds32f(sb + OFF_MROW + lane * 4);
                uint32_t ra, rbar;
                asm("mapa.shared::cluster.u32 %0, %1, %2;" : "=r"(ra) : "r"(sb + OFF_STAT + (lane ^ 8) * 8), "r"(rank ^ 1));
                asm("mapa.shared::cluster.u32 %0, %1, %2;" : "=r"(rbar) : "r"(sb + BAR_STAT), "r"(rank ^ 1));
                asm volatile("st.async.weak.shared::cluster.mbarrier::complete_tx::bytes.v2.f32 [%0], {%1,%2}, [%3];"
                             ::"r"(ra), "f"(m), "f"(l), "r"(rbar) : "memory");
                mbar_wait(sb + BAR_STAT, 0);
                const float pm = lds32f(sb + OFF_STAT + lane * 8), pl = lds32f(sb + OFF_STAT + lane * 8 + 4);
                const float mm = fmaxf(m, pm);
                const float e = ex2(m - mm), pe = ex2(pm - mm);
                sts32f(sb + OFF_F + lane * 4, __fdividef(e, l * e + pl * pe));
            }
            __syncwarp();
            if (lane == 0) mbar_arrive(sb + BAR_F);
        }
        mbar_wait(sb + BAR_D, 0);
    } else {
        const int w = warp - 4;
        asm volatile("barrier.cluster.wait.acquire.aligned;" ::: "memory");
        uint4* const oo = &g_scr.o[(((bh & 7) * 4 + (lane >> 4)) * 4 + w) * 128 + (bh >> 3) * 16 + (lane & 15)];
        uint4* const oout0 = pin(oo + rank * 1024);
        uint4* const oout1 = pin(oo + (rank ^ 1) * 1024);
        const uint32_t la = pin(sb + OFF_ORECV + (w * 32 + lane) * 16), obar = pin(sb + BAR_O + 8 * w);
        uint32_t ra, rbar;
        asm volatile("mapa.shared::cluster.u32 %0, %1, %2;" : "=r"(ra) : "r"(la), "r"(rank ^ 1));
        asm volatile("mapa.shared::cluster.u32 %0, %1, %2;" : "=r"(rbar) : "r"(obar), "r"(rank ^ 1));
        float o[4][4], t[2][4][4];
#pragma unroll
        for (int j = 0; j < 16; j++) (&o[0][0])[j] = (&t[0][0][0])[j] = (&t[1][0][0])[j] = 0.f;
        const uint32_t voff = (w >> 1) * 8192 + (lane & 15) * 128;
        const int vc = (w & 1) * 4 + (lane >> 4), vx = lane & 7;
        const uint32_t v0 = pin(sb + voff + ((vc ^ vx) << 4)), v1 = pin(sb + voff + (((vc + 2) ^ vx) << 4));
        pkt_store(oout0, 0, 0, 0, 0, tag ^ 1);
        uint32_t p[4][4], b0[4][4], b1[4][4];
        float a0 = 0.f, a1 = 0.f;
        auto load_v = [&](int st) {
#pragma unroll
            for (int j = 0; j < 4; j++) {
                ldsm4t(b0[j], v0 + st * STAGE + j * 2048);
                ldsm4t(b1[j], v1 + st * STAGE + j * 2048);
            }
        };
        auto next_p = [&](int i) {
            const int slot = i % NP;
            mbar_wait(sb + BAR_PFULL + 8 * slot, (i / NP) & 1);
#pragma unroll
            for (int j = 0; j < 4; j++) lds128(p[j], sb + OFF_P + slot * 2048 + j * 512 + lane * 16);
            const float n0 = lds32f(sb + OFF_ALPHA + slot * 64 + g8 * 4), n1 = lds32f(sb + OFF_ALPHA + slot * 64 + 32 + g8 * 4);
            __syncwarp();
            if (lane == 0) mbar_arrive(sb + BAR_PEMPTY + 8 * slot);
#pragma unroll
            for (int j = 0; j < 4; j++) {
                o[j][0] = fmaf(o[j][0], a0, t[0][j][0] + t[1][j][0]); o[j][1] = fmaf(o[j][1], a0, t[0][j][1] + t[1][j][1]);
                o[j][2] = fmaf(o[j][2], a1, t[0][j][2] + t[1][j][2]); o[j][3] = fmaf(o[j][3], a1, t[0][j][3] + t[1][j][3]);
            }
            a0 = n0; a1 = n1;
        };
        auto pv = [&]() {
#pragma unroll
            for (int j = 0; j < 16; j++) (&t[0][0][0])[j] = (&t[1][0][0])[j] = 0.f;
#pragma unroll
            for (int j = 0; j < 4; j++) {
                mma(t[j & 1][0], p[j], b0[j][0], b0[j][1]);
                mma(t[j & 1][1], p[j], b0[j][2], b0[j][3]);
                mma(t[j & 1][2], p[j], b1[j][0], b1[j][1]);
                mma(t[j & 1][3], p[j], b1[j][2], b1[j][3]);
            }
        };
        int st = KA + 1;
        uint32_t par = 0;
#pragma unroll 1
        for (int i = 0; i < NT - 1; i++) {
            mbar_wait(sb + BAR_FULL + 8 * st, par);
            load_v(st);
            next_p(i);
            pv();
            __syncwarp();
            if (lane == 0) mbar_arrive(sb + BAR_EMPTY + 8 * st);
            st += i < NT - KA - 1 ? 2 : 1;
            if (st >= NST) { st -= NST; par ^= 1; }
        }
        constexpr int LST = (2 * NT - 1) % NST, LPAR = ((2 * NT - 1) / NST) & 1;
        const bool landed = mbar_test(sb + BAR_FULL + 8 * LST, LPAR);
        if (landed) load_v(LST);
        next_p(NT - 1);
        mbar_wait(sb + BAR_F, 0);
        const float f0 = lds32f(sb + OFF_F + g8 * 4), f1 = lds32f(sb + OFF_F + 32 + g8 * 4);
        a0 *= f0; a1 *= f1;
#pragma unroll
        for (int j = 0; j < 4; j++) {
            o[j][0] *= a0; o[j][1] *= a0; o[j][2] *= a1; o[j][3] *= a1;
            asm volatile("" : "+f"(o[j][0]), "+f"(o[j][1]), "+f"(o[j][2]), "+f"(o[j][3]));
        }
        if (!landed) {
            mbar_wait(sb + BAR_FULL + 8 * LST, LPAR);
            load_v(LST);
        }
        auto finish = [&]() {
            pv();
#pragma unroll
            for (int j = 0; j < 4; j++) {
                o[j][0] = fmaf(t[0][j][0] + t[1][j][0], f0, o[j][0]); o[j][1] = fmaf(t[0][j][1] + t[1][j][1], f0, o[j][1]);
                o[j][2] = fmaf(t[0][j][2] + t[1][j][2], f1, o[j][2]); o[j][3] = fmaf(t[0][j][3] + t[1][j][3], f1, o[j][3]);
            }
        };
        auto send = [&]() {
#pragma unroll
            for (int k = 0; k < 4; k++) {
                const int e = k < 2 ? 2 : 0, j = (k & 1) * 2;
                asm volatile("st.async.weak.shared::cluster.mbarrier::complete_tx::bytes.v4.f32 [%0], {%1,%2,%3,%4}, [%5];"
                             ::"r"(ra + k * 2048), "f"(o[j][e]), "f"(o[j][e + 1]), "f"(o[j + 1][e]), "f"(o[j + 1][e + 1]),
                               "r"(rbar + (k < 2 ? 0 : 32)) : "memory");
            }
        };
        auto publish = [&](uint4* dst, int e, const float4& r0, const float4& r1) {
            pkt_store(dst, pack_bf16(o[0][e] + r0.x, o[0][e + 1] + r0.y), pack_bf16(o[1][e] + r0.z, o[1][e + 1] + r0.w),
                      pack_bf16(o[2][e] + r1.x, o[2][e + 1] + r1.y), pack_bf16(o[3][e] + r1.z, o[3][e + 1] + r1.w), tag);
        };
        const bool ha = mbar_test(obar, 0), hb = mbar_test(obar + 32, 0);
        if (ha && hb) {
            const float4 r0 = lds128f(la), r1 = lds128f(la + 2048), r2 = lds128f(la + 4096), r3 = lds128f(la + 6144);
            finish();
            publish(oout0, 0, r0, r1);
            publish(oout1, 2, r2, r3);
            send();
        } else {
            finish();
            send();
            mbar_wait(obar, 0);
            const float4 r0 = lds128f(la), r1 = lds128f(la + 2048);
            publish(oout0, 0, r0, r1);
        }
        if (lane == 0) mbar_arrive(sb + BAR_D);
    }

    {
        uint32_t a[8][2][4];
        const int kr = (lane >> 4) * 8 + (lane & 7);
        const int wc = (lane >> 3) & 1, wx = (kr >> 1) & 3;
        const uint32_t wb0 = pin(sb + OFF_WO + (g * 128 + kr) * 64 + ((wc ^ wx) << 4));
        const uint32_t wb1 = pin(sb + OFF_WO + (g * 128 + kr) * 64 + (((wc + 2) ^ wx) << 4));
        const uint32_t red = pin(sb + OFF_PRED + rh * 8192 + lane * 16);
        const uint32_t rw = pin(red + g * 512), rr = pin(red + (g & 1) * 4096 + (g >> 1) * 2048);
        const uint32_t wobar = sb + BAR_WO + 8 * g;
        constexpr uint32_t wopar = 0;
        auto wo_within = [&](uint32_t clks) {
            uint32_t c0, c1;
            bool in;
            asm volatile("mov.u32 %0, %%clock;" : "=r"(c0));
            do {
                in = mbar_test(wobar, wopar);
                asm volatile("mov.u32 %0, %%clock;" : "=r"(c1));
            } while (!in && c1 - c0 < clks);
            return in;
        };
        Pkt v[8];
        const bool in0 = wo_within(O_DELAY);
        pkt_issue<8, 4, 128, 32>(v, oin);
        if (!in0) {
#pragma unroll 1
            for (int it = 0; !wo_within(O_PERIOD); it++) {
                uint32_t b[8];
#pragma unroll
                for (int i = 0; i < 8; i++) b[i] = v[i].bad(tag);
                if (it > (1 << 16)) __trap();
#pragma unroll
                for (int i = 0; i < 8; i++) pkt_reload(v[i], oin + (i >> 2) * 32 + (i & 3) * 128, b[i]);
            }
        }
#pragma unroll
        for (int ks = 0; ks < 8; ks++) {
            ldsm4t(a[ks][0], wb0 + ks * 1024);
            ldsm4t(a[ks][1], wb1 + ks * 1024);
        }
        pkt_poll<8, 4, 128, 32>(v, oin, tag | (a[7][1][3] & zero));
        float c[2][2][2][4];
#pragma unroll
        for (int j = 0; j < 32; j++) (&c[0][0][0][0])[j] = 0.f;
#pragma unroll
        for (int dq = 0; dq < 4; dq++)
#pragma unroll
            for (int t = 0; t < 2; t++) {
                mma(c[t][0][0], a[2 * dq][0], v[t * 4 + dq].w0(), v[t * 4 + dq].w1());
                mma(c[t][1][0], a[2 * dq][1], v[t * 4 + dq].w0(), v[t * 4 + dq].w1());
                mma(c[t][0][1], a[2 * dq + 1][0], v[t * 4 + dq].w2(), v[t * 4 + dq].w3());
                mma(c[t][1][1], a[2 * dq + 1][1], v[t * 4 + dq].w2(), v[t * 4 + dq].w3());
            }
#pragma unroll
        for (int t = 0; t < 2; t++)
#pragma unroll
            for (int mt = 0; mt < 2; mt++)
                sts128f(rw + t * 4096 + mt * 2048, c[t][mt][0][0] + c[t][mt][1][0], c[t][mt][0][1] + c[t][mt][1][1],
                        c[t][mt][0][2] + c[t][mt][1][2], c[t][mt][0][3] + c[t][mt][1][3]);
        bar_sync(3 + rh, 128);
        const float4 s0 = lds128f(rr), s1 = lds128f(rr + 512), s2 = lds128f(rr + 1024), s3 = lds128f(rr + 1536);
        pkt_store(pout, __float_as_uint((s0.x + s1.x) + (s2.x + s3.x)), __float_as_uint((s0.y + s1.y) + (s2.y + s3.y)),
                  __float_as_uint((s0.z + s1.z) + (s2.z + s3.z)), __float_as_uint((s0.w + s1.w) + (s2.w + s3.w)), tag);
    }

    {
        if (warp < 4) {
            Pkt v[2];
            spin(P_DELAY);
            pkt_load(v[0], pin_);
            pkt_load(v[1], pin_ + 128);
#pragma unroll 1
            for (int it = 0;; it++) {
                const uint32_t b0 = v[0].bad(tag), b1 = v[1].bad(tag);
                if (!any_bit0(or3(b0, b1, 0u))) break;
                pkt_reload(v[0], pin_, b0);
                pkt_reload(v[1], pin_ + 128, b1);
                if (it > (1 << 20)) __trap();
            }
            const float e0 = __uint_as_float(v[0].w0()) + __uint_as_float(v[1].w0()), e1 = __uint_as_float(v[0].w1()) + __uint_as_float(v[1].w1());
            const float e2 = __uint_as_float(v[0].w2()) + __uint_as_float(v[1].w2()), e3 = __uint_as_float(v[0].w3()) + __uint_as_float(v[1].w3());
            const bool hi = lane & 8, hi2 = lane & 16;
            const float k0 = (hi ? e1 : e0) + __shfl_xor_sync(0xffffffffu, hi ? e0 : e1, 8);
            const float k1 = (hi ? e3 : e2) + __shfl_xor_sync(0xffffffffu, hi ? e2 : e3, 8);
            const uint32_t res = pack_bf16((hi2 ? k1 : k0) + __shfl_xor_sync(0xffffffffu, hi2 ? k0 : k1, 16), 0.f);
            asm volatile("st.global.u16 [%0], %1;" ::"l"(optr), "h"((uint16_t)res) : "memory");
        }
        if ((cta | warp | lane) == 0)
            asm volatile("st.relaxed.gpu.global.u32 [%0], %1;" ::"l"(&g_scr.epoch), "r"(epoch + 1) : "memory");
        if (warp >= 4) mbar_wait(sb + BAR_G + 8 * (warp - 4), 0);
    }
}

__device__ float g_fq[32 * 4096], g_fo[32 * 4096];
__global__ void fb_proj(const __nv_bfloat16* a_bf, const float* a_f, const __nv_bfloat16* w, int K, int N, float* o_f,
                        __nv_bfloat16* o_bf) {
    const int c = blockIdx.x * blockDim.x + threadIdx.x, r = blockIdx.y;
    float s = 0.f;
    for (int k = 0; k < K; k++) s += (a_bf ? __bfloat162float(a_bf[r * K + k]) : a_f[r * K + k]) * __bfloat162float(w[k * N + c]);
    if (o_bf) o_bf[r * N + c] = __float2bfloat16(s);
    else o_f[r * N + c] = __bfloat162float(__float2bfloat16(s));
}
__global__ void fb_attn(const __nv_bfloat16* kc, const __nv_bfloat16* vc) {
    __shared__ float sc[2048], red[128];
    const int r = blockIdx.x, hq = blockIdx.y, t = threadIdx.x;
    const size_t base = (size_t)((r >> 2) * 8 + (hq >> 2)) * 2048 * 128;
    float m = -INFINITY, l = 0.f, acc = 0.f;
    for (int j = t; j < 2048; j += 128) {
        float s = 0.f;
        for (int d = 0; d < 128; d++) s += g_fq[r * 4096 + hq * 128 + d] * __bfloat162float(kc[base + j * 128 + d]);
        sc[j] = s * 0.08838834764831845f;
        m = fmaxf(m, sc[j]);
    }
    red[t] = m;
    __syncthreads();
    for (int i = 0; i < 128; i++) m = fmaxf(m, red[i]);
    for (int j = t; j < 2048; j += 128) sc[j] = __expf(sc[j] - m);
    __syncthreads();
    for (int j = 0; j < 2048; j++) {
        l += sc[j];
        acc += sc[j] * __bfloat162float(vc[base + j * 128 + t]);
    }
    g_fo[r * 4096 + hq * 128 + t] = __bfloat162float(__float2bfloat16(acc / l));
}

typedef CUresult (*EncodeFn)(CUtensorMap*, CUtensorMapDataType, cuuint32_t, void*, const cuuint64_t*, const cuuint64_t*,
                             const cuuint32_t*, const cuuint32_t*, CUtensorMapInterleave, CUtensorMapSwizzle,
                             CUtensorMapL2promotion, CUtensorMapFloatOOBfill);

static void encode(EncodeFn fn, CUtensorMap* m, void* p, int rank, const cuuint64_t* dims, const cuuint64_t* strides,
                   const cuuint32_t* box, CUtensorMapSwizzle sw) {
    const cuuint32_t es[3] = {1, 1, 1};
    fn(m, CU_TENSOR_MAP_DATA_TYPE_BFLOAT16, rank, p, dims, strides, box, es, CU_TENSOR_MAP_INTERLEAVE_NONE, sw,
       CU_TENSOR_MAP_L2_PROMOTION_L2_256B, CU_TENSOR_MAP_FLOAT_OOB_FILL_NONE);
}

}

extern "C" void kernel_launch(void* const* d_in, const int* in_sizes, int n_in, void* d_out, int out_size) {
    using namespace gqa;
    static EncodeFn fn = nullptr;
    static uint32_t slot_ns = SLOT_NS;
    static bool fits = false;
    if (!fn) {
        int dev = 0, khz = 0, bits = 0;
        cudaGetDevice(&dev);
        cudaDeviceGetAttribute(&khz, cudaDevAttrMemoryClockRate, dev);
        cudaDeviceGetAttribute(&bits, cudaDevAttrGlobalMemoryBusWidth, dev);
        if (khz > 0 && bits > 0) slot_ns = (uint32_t)((double)NCTA * STAGE / (0.955 * 2.0 * khz * 1e-6 * (bits / 8)));
        void* p = nullptr;
        cudaDriverEntryPointQueryResult qr;
        cudaGetDriverEntryPoint("cuTensorMapEncodeTiled", &p, cudaEnableDefault, &qr);
        fn = (EncodeFn)p;
        cudaFuncSetAttribute(gqa_kernel, cudaFuncAttributeMaxDynamicSharedMemorySize, SMEM_BYTES);
        cudaLaunchConfig_t cfg = {};
        cfg.gridDim = dim3(NCTA);
        cfg.blockDim = dim3(288);
        cfg.dynamicSmemBytes = SMEM_BYTES;
        int clusters = 0;
        fits = cudaOccupancyMaxActiveClusters(&clusters, gqa_kernel, &cfg) == cudaSuccess && clusters >= NCTA / 2;
    }
    if (!fits) {
        float *fq = nullptr, *fo = nullptr;
        cudaGetSymbolAddress((void**)&fq, g_fq);
        cudaGetSymbolAddress((void**)&fo, g_fo);
        fb_proj<<<dim3(16, 32), 256, 0, cudaStreamPerThread>>>((const __nv_bfloat16*)d_in[0], nullptr, (const __nv_bfloat16*)d_in[3], 512,
                                                               4096, fq, nullptr);
        fb_attn<<<dim3(32, 32), 128, 0, cudaStreamPerThread>>>((const __nv_bfloat16*)d_in[1], (const __nv_bfloat16*)d_in[2]);
        fb_proj<<<dim3(2, 32), 256, 0, cudaStreamPerThread>>>(nullptr, fo, (const __nv_bfloat16*)d_in[4], 4096, 512, nullptr,
                                                              (__nv_bfloat16*)d_out);
        return;
    }
    CUtensorMap tmK, tmV, tmX, tmWq, tmWo;
    {
        const cuuint64_t dims[3] = {64, 8 * 8 * 2048, 2}, str[2] = {256, 128};
        const cuuint32_t box[3] = {64, 64, 2};
        encode(fn, &tmK, d_in[1], 3, dims, str, box, CU_TENSOR_MAP_SWIZZLE_128B);
        encode(fn, &tmV, d_in[2], 3, dims, str, box, CU_TENSOR_MAP_SWIZZLE_128B);
    }
    {
        const cuuint64_t dims[3] = {64, 32, 8}, str[2] = {1024, 128};
        const cuuint32_t box[3] = {64, 32, 8};
        encode(fn, &tmX, d_in[0], 3, dims, str, box, CU_TENSOR_MAP_SWIZZLE_128B);
    }
    {
        const cuuint64_t dq[2] = {4096, 512}, sq[1] = {8192}, dw[2] = {512, 4096}, sw[1] = {1024};
        const cuuint32_t box[2] = {32, 256};
        encode(fn, &tmWq, d_in[3], 2, dq, sq, box, CU_TENSOR_MAP_SWIZZLE_64B);
        const cuuint32_t boxo[2] = {32, 128};
        encode(fn, &tmWo, d_in[4], 2, dw, sw, boxo, CU_TENSOR_MAP_SWIZZLE_64B);
    }
    gqa_kernel<<<NCTA, 288, SMEM_BYTES, cudaStreamPerThread>>>(Ptrs{{(const uint8_t*)d_in[3], nullptr}}, (__nv_bfloat16*)d_out, slot_ns, 0u, tmK, tmV, tmX,
                                                               tmWq, tmWo);
}
```

```cpp
#include <cuda_runtime.h>
#include <cuda_bf16.h>
#include <cuda.h>
#include <stdint.h>

namespace gqa {

constexpr int PA_NS = 2320;
constexpr int SLOT_NS = 655;
constexpr int WO_SLOT = 2980;
constexpr int WO_STEP = 60;
constexpr int Q_DELAY_NS = 1000;
constexpr int O_DELAY = 900;
constexpr int O_PERIOD = 800;
constexpr int P_DELAY = 330;
constexpr int PF_BYTES = 8192;

constexpr int NCTA = 128;
constexpr int NT = 16;
constexpr int NST = 13;
constexpr int NST0 = 10;
constexpr int WIN0 = 3;
constexpr int WIN = 6;
constexpr int WSW = 8;
constexpr int KA = 2;
constexpr int NP = 4;
constexpr int STAGE = 16384;

constexpr int OFF_WQ = NST0 * STAGE;
constexpr int OFF_X = OFF_WQ + 32768;
constexpr int OFF_QRED = OFF_X;
constexpr int OFF_WO = ((2 * NT) % NST) * STAGE;
constexpr int OFF_P = NST * STAGE;
constexpr int OFF_ORECV = (((2 * NT) % NST) + 3) * STAGE;
constexpr int OFF_ALPHA = OFF_P + NP * 2048;
constexpr int OFF_WMAX = OFF_ALPHA + NP * 64;
constexpr int OFF_LSUM = OFF_WMAX + 512;
constexpr int OFF_MROW = OFF_LSUM + 256;
constexpr int OFF_STAT = OFF_MROW + 64;
constexpr int OFF_F = OFF_STAT + 128;
constexpr int OFF_PRED = (((2 * NT) % NST) + 2) * STAGE;
constexpr int OFF_BAR = (NST + 1) * STAGE;
constexpr int BAR_FULL = OFF_BAR;
constexpr int BAR_EMPTY = BAR_FULL + 8 * NST;
constexpr int BAR_PFULL = BAR_EMPTY + 8 * NST;
constexpr int BAR_PEMPTY = BAR_PFULL + 8 * NP;
constexpr int BAR_W = BAR_PEMPTY + 8 * NP;
constexpr int BAR_STAT = BAR_W + 8;
constexpr int BAR_F = BAR_STAT + 8;
constexpr int BAR_O = BAR_F + 8;
constexpr int BAR_G = BAR_O + 32;
constexpr int BAR_D = BAR_G + 32;
constexpr int BAR_WO = BAR_D + 8;
constexpr int SMEM_BYTES = OFF_BAR + 512;
static_assert(OFF_F + 64 <= OFF_BAR, "scratch overflows its slot");
static_assert(BAR_WO + 32 <= SMEM_BYTES, "barriers overflow");
static_assert((2 * NT) % NST + 3 < NST, "wo / partial slots must not wrap");
static_assert(SMEM_BYTES <= 232448, "too much shared memory");

struct __align__(1024) Scratch {
    uint4 q[32 * 4 * 8 * 16];
    uint4 o[32 * 4 * 8 * 16];
    uint4 p[128 * 8 * 32];
    unsigned epoch;
    float fq[32 * 4096], fo[32 * 4096];
};
__device__ Scratch g_scr;

__device__ __forceinline__ void mbar_init(uint32_t bar, uint32_t cnt) {
    asm volatile("mbarrier.init.shared::cta.b64 [%0], %1;" ::"r"(bar), "r"(cnt) : "memory");
}
__device__ __forceinline__ void mbar_expect_tx(uint32_t bar, uint32_t bytes) {
    asm volatile("mbarrier.arrive.expect_tx.shared::cta.b64 _, [%0], %1;" ::"r"(bar), "r"(bytes) : "memory");
}
__device__ __forceinline__ void mbar_arrive(uint32_t bar) {
    asm volatile("mbarrier.arrive.shared::cta.b64 _, [%0];" ::"r"(bar) : "memory");
}
__device__ __forceinline__ bool mbar_try(uint32_t bar, uint32_t parity) {
    uint32_t ok;
    asm volatile("{\n.reg .pred p;\nmbarrier.try_wait.parity.shared::cta.b64 p, [%1], %2;\nselp.u32 %0, 1, 0, p;\n}"
                 : "=r"(ok) : "r"(bar), "r"(parity) : "memory");
    return ok;
}
__device__ __forceinline__ bool mbar_test(uint32_t bar, uint32_t parity) {
    uint32_t ok;
    asm volatile("{\n.reg .pred p;\nmbarrier.test_wait.parity.shared::cta.b64 p, [%1], %2;\nselp.u32 %0, 1, 0, p;\n}"
                 : "=r"(ok) : "r"(bar), "r"(parity) : "memory");
    return ok;
}
__device__ __forceinline__ void mbar_wait(uint32_t bar, uint32_t parity) {
#pragma unroll 1
    for (int i = 0; !mbar_try(bar, parity); i++)
        if (i > (1 << 20)) __trap();
}
__device__ __forceinline__ void tma2d(uint32_t dst, const CUtensorMap* m, int c0, int c1, uint32_t bar) {
    asm volatile("cp.async.bulk.tensor.2d.shared::cluster.global.mbarrier::complete_tx::bytes [%0], [%1, {%3, %4}], [%2];"
                 ::"r"(dst), "l"(m), "r"(bar), "r"(c0), "r"(c1) : "memory");
}
__device__ __forceinline__ void tma3d(uint32_t dst, const CUtensorMap* m, int c0, int c1, int c2, uint32_t bar) {
    asm volatile("cp.async.bulk.tensor.3d.shared::cluster.global.mbarrier::complete_tx::bytes [%0], [%1, {%3, %4, %5}], [%2];"
                 ::"r"(dst), "l"(m), "r"(bar), "r"(c0), "r"(c1), "r"(c2) : "memory");
}
__device__ __forceinline__ void tma3d_hint(uint32_t dst, const CUtensorMap* m, int c0, int c1, int c2, uint32_t bar, uint64_t pol) {
    asm volatile("cp.async.bulk.tensor.3d.shared::cluster.global.mbarrier::complete_tx::bytes.L2::cache_hint [%0], [%1, {%3, %4, %5}], [%2], %6;"
                 ::"r"(dst), "l"(m), "r"(bar), "r"(c0), "r"(c1), "r"(c2), "l"(pol) : "memory");
}
__device__ __forceinline__ void ldsm4(uint32_t (&r)[4], uint32_t addr) {
    asm volatile("ldmatrix.sync.aligned.m8n8.x4.shared.b16 {%0,%1,%2,%3}, [%4];"
                 : "=r"(r[0]), "=r"(r[1]), "=r"(r[2]), "=r"(r[3]) : "r"(addr) : "memory");
}
__device__ __forceinline__ void ldsm4t(uint32_t (&r)[4], uint32_t addr) {
    asm volatile("ldmatrix.sync.aligned.m8n8.x4.trans.shared.b16 {%0,%1,%2,%3}, [%4];"
                 : "=r"(r[0]), "=r"(r[1]), "=r"(r[2]), "=r"(r[3]) : "r"(addr) : "memory");
}
__device__ __forceinline__ void mma(float (&c)[4], const uint32_t (&a)[4], uint32_t b0, uint32_t b1) {
    asm volatile("mma.sync.aligned.m16n8k16.row.col.f32.bf16.bf16.f32 {%0,%1,%2,%3}, {%4,%5,%6,%7}, {%8,%9}, {%0,%1,%2,%3};"
                 : "+f"(c[0]), "+f"(c[1]), "+f"(c[2]), "+f"(c[3])
                 : "r"(a[0]), "r"(a[1]), "r"(a[2]), "r"(a[3]), "r"(b0), "r"(b1));
}
__device__ __forceinline__ uint32_t pack_bf16(float lo, float hi) {
    uint32_t r;
    asm("cvt.rn.bf16x2.f32 %0, %1, %2;" : "=r"(r) : "f"(hi), "f"(lo));
    return r;
}
__device__ __forceinline__ float ex2(float x) {
    float y;
    asm("ex2.approx.ftz.f32 %0, %1;" : "=f"(y) : "f"(x));
    return y;
}
__device__ __forceinline__ void sts128(uint32_t addr, uint32_t a, uint32_t b, uint32_t c, uint32_t d) {
    asm volatile("st.shared.v4.b32 [%0], {%1,%2,%3,%4};" ::"r"(addr), "r"(a), "r"(b), "r"(c), "r"(d) : "memory");
}
__device__ __forceinline__ void sts128f(uint32_t addr, float a, float b, float c, float d) {
    asm volatile("st.shared.v4.f32 [%0], {%1,%2,%3,%4};" ::"r"(addr), "f"(a), "f"(b), "f"(c), "f"(d) : "memory");
}
__device__ __forceinline__ void sts32f(uint32_t addr, float a) {
    asm volatile("st.shared.f32 [%0], %1;" ::"r"(addr), "f"(a) : "memory");
}
__device__ __forceinline__ void lds128(uint32_t (&r)[4], uint32_t addr) {
    asm volatile("ld.shared.v4.b32 {%0,%1,%2,%3}, [%4];" : "=r"(r[0]), "=r"(r[1]), "=r"(r[2]), "=r"(r[3]) : "r"(addr) : "memory");
}
__device__ __forceinline__ float4 lds128f(uint32_t addr) {
    float4 v;
    asm volatile("ld.shared.v4.f32 {%0,%1,%2,%3}, [%4];" : "=f"(v.x), "=f"(v.y), "=f"(v.z), "=f"(v.w) : "r"(addr) : "memory");
    return v;
}
__device__ __forceinline__ float lds32f(uint32_t addr) {
    float v;
    asm volatile("ld.shared.f32 %0, [%1];" : "=f"(v) : "r"(addr) : "memory");
    return v;
}
__device__ __forceinline__ void bar_sync(int id, int n) { asm volatile("bar.sync %0, %1;" ::"r"(id), "r"(n) : "memory"); }
template <typename T> __device__ __forceinline__ T* pin(T* p) { asm volatile("" : "+l"(p)); return p; }
__device__ __forceinline__ uint32_t pin(uint32_t v) { asm volatile("" : "+r"(v)); return v; }

struct Pkt {
    uint64_t lo, hi;
    __device__ __forceinline__ uint32_t w0() const { return (uint32_t)lo; }
    __device__ __forceinline__ uint32_t w1() const { return (uint32_t)(lo >> 32); }
    __device__ __forceinline__ uint32_t w2() const { return (uint32_t)hi; }
    __device__ __forceinline__ uint32_t w3() const { return (uint32_t)(hi >> 32); }
    __device__ __forceinline__ uint32_t bad(uint32_t tag) const {
        uint32_t r;
        asm("lop3.b32 %0, %1, %2, %3, 0x7E;" : "=r"(r) : "r"(w0()), "r"(w2()), "r"(tag));
        return r;
    }
};
__device__ __forceinline__ void pkt_store(uint4* p, uint32_t a, uint32_t b, uint32_t c, uint32_t d, uint32_t tag) {
    a = (a & ~1u) | tag;
    c = (c & ~1u) | tag;
    asm volatile("{\n.reg .b64 lo, hi;\nmov.b64 lo, {%1,%2};\nmov.b64 hi, {%3,%4};\n"
                 "st.relaxed.gpu.global.v2.b64 [%0], {lo, hi};\n}" ::"l"(p), "r"(a), "r"(b), "r"(c), "r"(d) : "memory");
}
__device__ __forceinline__ void pkt_load(Pkt& v, const uint4* p) {
    asm volatile("ld.relaxed.gpu.global.v2.b64 {%0, %1}, [%2];" : "=l"(v.lo), "=l"(v.hi) : "l"(p) : "memory");
}
__device__ __forceinline__ void pkt_reload(Pkt& v, const uint4* p, uint32_t bad) {
    asm volatile("{\n.reg .pred p;\n.reg .b32 t;\nand.b32 t, %3, 1;\nsetp.ne.u32 p, t, 0;\n"
                 "@p ld.relaxed.gpu.global.v2.b64 {%0, %1}, [%2];\n}"
                 : "+l"(v.lo), "+l"(v.hi) : "l"(p), "r"(bad) : "memory");
}
__device__ __forceinline__ uint32_t or3(uint32_t a, uint32_t b, uint32_t c) {
    uint32_t r;
    asm("lop3.b32 %0, %1, %2, %3, 0xFE;" : "=r"(r) : "r"(a), "r"(b), "r"(c));
    return r;
}
__device__ __forceinline__ bool any_bit0(uint32_t x) {
    uint32_t r;
    asm volatile("{\n.reg .pred p, q;\n.reg .b32 t;\nand.b32 t, %1, 1;\nsetp.ne.u32 p, t, 0;\nvote.sync.any.pred q, p, 0xffffffff;\n"
                 "selp.u32 %0, 1, 0, q;\n}" : "=r"(r) : "r"(x));
    return r;
}
template <int N, int N0, int S0, int S1>
__device__ __forceinline__ void pkt_issue(Pkt (&v)[N], const uint4* p) {
#pragma unroll
    for (int i = 0; i < N; i++) pkt_load(v[i], p + (i / N0) * S1 + (i % N0) * S0);
}
template <int N, int N0, int S0, int S1>
__device__ __forceinline__ void pkt_poll(Pkt (&v)[N], const uint4* p, uint32_t tag) {
    static_assert(N == 1 || N == 8, "");
#pragma unroll 1
    for (int it = 0;; it++) {
        uint32_t b[N];
#pragma unroll
        for (int i = 0; i < N; i++) b[i] = v[i].bad(tag);
        uint32_t bad = b[0];
        if (N == 8) bad = or3(or3(b[0], b[1 % N], b[2 % N]), or3(b[3 % N], b[4 % N], b[5 % N]), or3(b[6 % N], b[7 % N], 0u));
        if (!any_bit0(bad)) break;
#pragma unroll
        for (int i = 0; i < N; i++) pkt_reload(v[i], p + (i / N0) * S1 + (i % N0) * S0, b[i]);
        if (it > (1 << 20)) __trap();
    }
}

__device__ __forceinline__ uint32_t now_ns() {
    uint32_t t;
    asm volatile("mov.u32 %0, %%globaltimer_lo;" : "=r"(t));
    return t;
}
__device__ __forceinline__ void spin(uint32_t clks) {
    uint32_t c0, c1;
    asm volatile("mov.u32 %0, %%clock;" : "=r"(c0));
    do { asm volatile("mov.u32 %0, %%clock;" : "=r"(c1)); } while (c1 - c0 < clks);
}
__device__ __forceinline__ void wait_until(uint32_t t) {
#pragma unroll 1
    for (int i = 0; (int)(now_ns() - t) < 0 && i < (1 << 16); i++) {}
}

struct Ptrs { const uint8_t* p[2]; };

__global__ void __cluster_dims__(2, 1, 1) __launch_bounds__(288, 1)
gqa_kernel(const __grid_constant__ Ptrs ptrs, __nv_bfloat16* __restrict__ out, uint32_t slot_ns, uint32_t zero,
           const __grid_constant__ CUtensorMap tmK, const __grid_constant__ CUtensorMap tmV,
           const __grid_constant__ CUtensorMap tmX, const __grid_constant__ CUtensorMap tmWq,
           const __grid_constant__ CUtensorMap tmWo) {
    const uint32_t tstart = now_ns();
    if (threadIdx.x == 32)
        asm volatile("cp.async.bulk.prefetch.L2.global [%0], %1;" ::"l"(ptrs.p[blockIdx.x >> 10] + blockIdx.x * PF_BYTES), "r"(PF_BYTES)
                     : "memory");
    extern __shared__ __align__(1024) uint8_t smem_raw[];
    const uint32_t sb = pin((uint32_t)__cvta_generic_to_shared(smem_raw));
    if (threadIdx.x == 0) {
        mbar_init(sb + BAR_W, 1);
        asm volatile("fence.mbarrier_init.release.cluster;" ::: "memory");
        mbar_expect_tx(sb + BAR_W, 65536);
        tma2d(sb + OFF_WQ, &tmWq, blockIdx.x * 32, 0, sb + BAR_W);
        tma2d(sb + OFF_WQ + 16384, &tmWq, blockIdx.x * 32, 256, sb + BAR_W);
        tma3d(sb + OFF_X, &tmX, 0, 0, 0, sb + BAR_W);
    }
    const int warp = __shfl_sync(0xffffffffu, threadIdx.x >> 5, 0), lane = pin(threadIdx.x & 31);
    const int cta = pin(blockIdx.x), rank = cta & 1, bh = cta >> 1;

    if (warp == 8) {
        const int row0 = bh * 2048 + rank * 64;
        uint64_t pol;
        asm volatile("createpolicy.fractional.L2::evict_first.b64 %0, 1.0;" : "=l"(pol));
        auto issue = [&](int n) {
            const bool isv = n >= 2 * NT - KA || (n >= KA && ((n - KA) & 1));
            const int t = n < KA ? n : n >= 2 * NT - KA ? n - NT : isv ? (n - KA) >> 1 : (n + KA) >> 1;
            const int st = n % NST;
            tma3d_hint(sb + st * STAGE, isv ? &tmV : &tmK, 0, row0 + t * 128, 0, sb + BAR_FULL + 8 * st, pol);
        };
        if (lane == 0) {
            if (sb & 1023) __trap();
#pragma unroll
            for (int i = 0; i < WIN0; i++) mbar_init(sb + BAR_FULL + 8 * i, 1);
            asm volatile("fence.mbarrier_init.release.cluster;" ::: "memory");
#pragma unroll
            for (int n = 0; n < WIN0; n++) {
                mbar_expect_tx(sb + BAR_FULL + 8 * n, STAGE);
                issue(n);
            }
            for (int i = WIN0; i < NST; i++) mbar_init(sb + BAR_FULL + 8 * i, 1);
            for (int i = 0; i < NST; i++) mbar_init(sb + BAR_EMPTY + 8 * i, 4);
            for (int i = 0; i < NP; i++) {
                mbar_init(sb + BAR_PFULL + 8 * i, 4);
                mbar_init(sb + BAR_PEMPTY + 8 * i, 4);
            }
            mbar_init(sb + BAR_STAT, 1);
            mbar_init(sb + BAR_F, 1);
            mbar_init(sb + BAR_D, 4);
            mbar_expect_tx(sb + BAR_STAT, 128);
            for (int i = 0; i < 4; i++) {
                mbar_init(sb + BAR_O + 8 * i, 1);
                mbar_expect_tx(sb + BAR_O + 8 * i, 1024);
                mbar_init(sb + BAR_G + 8 * i, 1);
                mbar_expect_tx(sb + BAR_G + 8 * i, 1024);
                mbar_init(sb + BAR_WO + 8 * i, 1);
                mbar_expect_tx(sb + BAR_WO + 8 * i, 8192);
            }
            asm volatile("fence.mbarrier_init.release.cluster;" ::: "memory");
            asm volatile("prefetch.tensormap [%0];" ::"l"(&tmWo) : "memory");
        }
        __syncthreads();
        asm volatile("barrier.cluster.arrive.relaxed.aligned;" ::: "memory");
        if (lane == 0) {
            auto wait_free = [&](int n) {
                const int st = n % NST, k = n / NST;
                if (st >= NST0) mbar_wait(sb + BAR_EMPTY + 8 * st, k & 1);
                else if (k) mbar_wait(sb + BAR_EMPTY + 8 * st, (k - 1) & 1);
            };
            const uint32_t t3 = tstart + PA_NS;
#pragma unroll
            for (int n = WIN0; n < 2 * NT; n++) {
                wait_free(n);
                mbar_expect_tx(sb + BAR_FULL + 8 * (n % NST), STAGE);
                if (n < WSW || n >= WSW + WIN - WIN0) {
                    const int d = n - (n < WSW ? WIN0 : WIN);
                    mbar_wait(sb + BAR_FULL + 8 * (d % NST), (d / NST) & 1);
                }
                if (n >= WSW) wait_until(t3 + (n - 3) * slot_ns);
                issue(n);
            }
            wait_free(2 * NT); wait_free(2 * NT + 1); wait_free(2 * NT + 2);
#pragma unroll
            for (int g = 0; g < 4; g++) {
                wait_until(t3 + (WO_SLOT + g * WO_STEP) * slot_ns / 100);
                tma2d(sb + OFF_WO + g * 8192, &tmWo, (cta & 15) * 32, (cta >> 4) * 512 + g * 128, sb + BAR_WO + 8 * g);
            }
        }
        return;
    }

    unsigned epoch;
    asm volatile("ld.relaxed.gpu.global.u32 %0, [%1];" : "=r"(epoch) : "l"(&g_scr.epoch) : "memory");
    const int g8 = lane >> 2, quad = lane & 3;
    const int rh = warp >> 2, g = (warp + 2 * rh) & 3;
    const uint4* const oin = pin(&g_scr.o[((cta >> 4) * 4 + g) * 512 + rh * 64 + lane]);
    uint4* const pout = pin(&g_scr.p[(((rh * 2 + (g & 1)) * 32 + (cta & 15) * 2 + (g >> 1)) * 8 + (cta >> 4)) * 32 + quad * 8 + g8]);
    const uint4* const pin_ = pin(&g_scr.p[(cta * 8 + (lane >> 3)) * 32 + (warp & 3) * 8 + (lane & 7)]);
    __nv_bfloat16* const optr = pin(out + ((cta >> 5) * 8 + (warp & 3) * 2 + ((lane >> 3) & 1)) * 512 + (cta & 31) * 16 + (lane & 7) +
                                    (lane >> 4) * 8);
    __syncthreads();

    {
        const int kq = warp & 3, mt = warp >> 2;
        float c[4][4];
#pragma unroll
        for (int j = 0; j < 4; j++) c[j][0] = c[j][1] = c[j][2] = c[j][3] = 0.f;
        const int ar = mt * 16 + (lane & 15);
        const uint32_t abase = sb + OFF_X + kq * 8192 + ar * 128;
        const int br = lane & 15;
        const uint32_t bbase = sb + OFF_WQ + (kq * 128 + br) * 64;
        if (warp < 4) pkt_store(&g_scr.q[cta * 128 + warp * 32 + lane], 0, 0, 0, 0, epoch & 1);
        pkt_store(pout, 0, 0, 0, 0, epoch & 1);
        mbar_wait(sb + BAR_W, 0);
#pragma unroll
        for (int ks = 0; ks < 8; ks++) {
            uint32_t a[4], b0[4], b1[4];
            ldsm4(a, abase + (ks >> 2) * 4096 + ((((ks & 3) * 2 + (lane >> 4)) ^ (ar & 7)) << 4));
            ldsm4t(b0, bbase + ks * 1024 + (((lane >> 4) ^ ((br >> 1) & 3)) << 4));
            ldsm4t(b1, bbase + ks * 1024 + (((2 + (lane >> 4)) ^ ((br >> 1) & 3)) << 4));
            mma(c[0], a, b0[0], b0[1]);
            mma(c[1], a, b0[2], b0[3]);
            mma(c[2], a, b1[0], b1[1]);
            mma(c[3], a, b1[2], b1[3]);
        }
        bar_sync(1, 256);
        asm volatile("barrier.cluster.arrive.relaxed.aligned;" ::: "memory");
        const uint32_t rb = sb + OFF_QRED + (kq * 2 + mt) * 2048 + lane * 16;
        sts128f(rb, c[0][0], c[0][1], c[1][0], c[1][1]);
        sts128f(rb + 512, c[2][0], c[2][1], c[3][0], c[3][1]);
        sts128f(rb + 1024, c[0][2], c[0][3], c[1][2], c[1][3]);
        sts128f(rb + 1536, c[2][2], c[2][3], c[3][2], c[3][3]);
        bar_sync(1, 256);
    }
    const uint32_t tag = pin((epoch + 1) & 1);

    if (warp < 4) {
        {
            const uint32_t rb = sb + OFF_QRED + warp * 1024 + lane * 16;
            float4 s0 = lds128f(rb), s1 = lds128f(rb + 512);
#pragma unroll
            for (int kq = 1; kq < 4; kq++) {
                float4 t0 = lds128f(rb + kq * 4096), t1 = lds128f(rb + kq * 4096 + 512);
                s0.x += t0.x; s0.y += t0.y; s0.z += t0.z; s0.w += t0.w;
                s1.x += t1.x; s1.y += t1.y; s1.z += t1.z; s1.w += t1.w;
            }
            pkt_store(&g_scr.q[cta * 128 + warp * 32 + lane], pack_bf16(s0.x, s0.y), pack_bf16(s0.z, s0.w),
                      pack_bf16(s1.x, s1.y), pack_bf16(s1.z, s1.w), tag);
            __syncwarp();
            if (lane < NST - NST0) mbar_arrive(sb + BAR_EMPTY + 8 * (NST0 + lane));
        }
        __nanosleep(Q_DELAY_NS);
        uint32_t q[8][4];
        {
            Pkt v[8];
            const uint4* qp = &g_scr.q[(((bh & 7) * 4 + (lane >> 4)) * 4) * 128 + (bh >> 3) * 16 + (lane & 15)];
            pkt_issue<8, 4, 128, 1024>(v, qp);
            pkt_poll<8, 4, 128, 1024>(v, qp, tag);
#pragma unroll
            for (int dq = 0; dq < 4; dq++) {
                const Pkt a = rank ? v[4 + dq] : v[dq], b = rank ? v[dq] : v[4 + dq];
                q[2 * dq][0] = a.w0();     q[2 * dq][1] = b.w0();     q[2 * dq][2] = a.w1();     q[2 * dq][3] = b.w1();
                q[2 * dq + 1][0] = a.w2(); q[2 * dq + 1][1] = b.w2(); q[2 * dq + 1][2] = a.w3(); q[2 * dq + 1][3] = b.w3();
            }
        }
        asm volatile("barrier.cluster.wait.acquire.aligned;" ::: "memory");
        constexpr float C = 0.08838834764831845f * 1.4426950408889634f;
        float mc0 = -INFINITY, mc1 = -INFINITY, l0 = 0.f, l1 = 0.f;
        const int key = warp * 16 + (lane >> 4) * 8 + (lane & 7);
        const uint32_t koff = key * 128;
        const int ksel = (lane >> 3) & 1, kx = lane & 7;
        int st = 0;
        uint32_t par = 0;
#pragma unroll 1
        for (int i = 0; i < NT; i++) {
            const uint32_t kb = sb + st * STAGE + koff;
            float s[2][2][4];
#pragma unroll
            for (int j = 0; j < 4; j++) s[0][0][j] = s[0][1][j] = s[1][0][j] = s[1][1][j] = 0.f;
            mbar_wait(sb + BAR_FULL + 8 * st, par);
#pragma unroll
            for (int ks = 0; ks < 8; ks++) {
                uint32_t b[4];
                ldsm4(b, kb + (ks >> 2) * 8192 + ((((ks & 3) * 2 + ksel) ^ kx) << 4));
                mma(s[ks & 1][0], q[ks], b[0], b[1]);
                mma(s[ks & 1][1], q[ks], b[2], b[3]);
            }
            __syncwarp();
            if (lane == 0) mbar_arrive(sb + BAR_EMPTY + 8 * st);
            st += i < KA ? 1 : 2;
            if (st >= NST) { st -= NST; par ^= 1; }
            float sv[2][4];
#pragma unroll
            for (int j = 0; j < 4; j++) { sv[0][j] = s[0][0][j] + s[1][0][j]; sv[1][j] = s[0][1][j] + s[1][1][j]; }
            float t0 = fmaxf(fmaxf(sv[0][0], sv[0][1]), fmaxf(sv[1][0], sv[1][1]));
            float t1 = fmaxf(fmaxf(sv[0][2], sv[0][3]), fmaxf(sv[1][2], sv[1][3]));
            t0 = fmaxf(t0, __shfl_xor_sync(0xffffffffu, t0, 1));
            t1 = fmaxf(t1, __shfl_xor_sync(0xffffffffu, t1, 1));
            t0 = fmaxf(t0, __shfl_xor_sync(0xffffffffu, t0, 2));
            t1 = fmaxf(t1, __shfl_xor_sync(0xffffffffu, t1, 2));
            const uint32_t wm = sb + OFF_WMAX + (i & 1) * 256 + g8 * 16;
            if (quad == 0) { sts32f(wm + warp * 4, t0); sts32f(wm + 128 + warp * 4, t1); }
            bar_sync(2, 128);
            const float4 w0 = lds128f(wm), w1 = lds128f(wm + 128);
            const float n0 = fmaxf(mc0, fmaxf(fmaxf(w0.x, w0.y), fmaxf(w0.z, w0.w)) * C);
            const float n1 = fmaxf(mc1, fmaxf(fmaxf(w1.x, w1.y), fmaxf(w1.z, w1.w)) * C);
            const float a0 = ex2(mc0 - n0), a1 = ex2(mc1 - n1);
            mc0 = n0; mc1 = n1;
            float p[2][4];
#pragma unroll
            for (int j = 0; j < 2; j++) {
                p[j][0] = ex2(fmaf(sv[j][0], C, -n0)); p[j][1] = ex2(fmaf(sv[j][1], C, -n0));
                p[j][2] = ex2(fmaf(sv[j][2], C, -n1)); p[j][3] = ex2(fmaf(sv[j][3], C, -n1));
            }
            l0 = l0 * a0 + ((p[0][0] + p[0][1]) + (p[1][0] + p[1][1]));
            l1 = l1 * a1 + ((p[0][2] + p[0][3]) + (p[1][2] + p[1][3]));
            const int slot = i % NP;
            if (i >= NP) mbar_wait(sb + BAR_PEMPTY + 8 * slot, (i / NP - 1) & 1);
            sts128(sb + OFF_P + slot * 2048 + warp * 512 + lane * 16, pack_bf16(p[0][0], p[0][1]), pack_bf16(p[0][2], p[0][3]),
                   pack_bf16(p[1][0], p[1][1]), pack_bf16(p[1][2], p[1][3]));
            if (warp == 0 && quad == 0) {
                sts32f(sb + OFF_ALPHA + slot * 64 + g8 * 4, a0);
                sts32f(sb + OFF_ALPHA + slot * 64 + 32 + g8 * 4, a1);
            }
            __syncwarp();
            if (lane == 0) mbar_arrive(sb + BAR_PFULL + 8 * slot);
        }
        l0 += __shfl_xor_sync(0xffffffffu, l0, 1);
        l1 += __shfl_xor_sync(0xffffffffu, l1, 1);
        l0 += __shfl_xor_sync(0xffffffffu, l0, 2);
        l1 += __shfl_xor_sync(0xffffffffu, l1, 2);
        if (quad == 0) {
            sts32f(sb + OFF_LSUM + g8 * 16 + warp * 4, l0);
            sts32f(sb + OFF_LSUM + 128 + g8 * 16 + warp * 4, l1);
            if (warp == 0) { sts32f(sb + OFF_MROW + g8 * 4, mc0); sts32f(sb + OFF_MROW + 32 + g8 * 4, mc1); }
        }
        bar_sync(2, 128);
        if (warp == 0) {
            if (lane < 16) {
                const float4 lv = lds128f(sb + OFF_LSUM + lane * 16);
                const float l = (lv.x + lv.y) + (lv.z + lv.w), m = lds32f(sb + OFF_MROW + lane * 4);
                uint32_t ra, rbar;
                asm("mapa.shared::cluster.u32 %0, %1, %2;" : "=r"(ra) : "r"(sb + OFF_STAT + (lane ^ 8) * 8), "r"(rank ^ 1));
                asm("mapa.shared::cluster.u32 %0, %1, %2;" : "=r"(rbar) : "r"(sb + BAR_STAT), "r"(rank ^ 1));
                asm volatile("st.async.weak.shared::cluster.mbarrier::complete_tx::bytes.v2.f32 [%0], {%1,%2}, [%3];"
                             ::"r"(ra), "f"(m), "f"(l), "r"(rbar) : "memory");
                mbar_wait(sb + BAR_STAT, 0);
                const float pm = lds32f(sb + OFF_STAT + lane * 8), pl = lds32f(sb + OFF_STAT + lane * 8 + 4);
                const float mm = fmaxf(m, pm);
                const float e = ex2(m - mm), pe = ex2(pm - mm);
                sts32f(sb + OFF_F + lane * 4, __fdividef(e, l * e + pl * pe));
            }
            __syncwarp();
            if (lane == 0) mbar_arrive(sb + BAR_F);
        }
        mbar_wait(sb + BAR_D, 0);
    } else {
        const int w = warp - 4;
        asm volatile("barrier.cluster.wait.acquire.aligned;" ::: "memory");
        uint4* const oo = &g_scr.o[(((bh & 7) * 4 + (lane >> 4)) * 4 + w) * 128 + (bh >> 3) * 16 + (lane & 15)];
        uint4* const oout0 = pin(oo + rank * 1024);
        uint4* const oout1 = pin(oo + (rank ^ 1) * 1024);
        const uint32_t la = pin(sb + OFF_ORECV + (w * 32 + lane) * 16), obar = pin(sb + BAR_O + 8 * w);
        uint32_t ra, rbar;
        asm volatile("mapa.shared::cluster.u32 %0, %1, %2;" : "=r"(ra) : "r"(la), "r"(rank ^ 1));
        asm volatile("mapa.shared::cluster.u32 %0, %1, %2;" : "=r"(rbar) : "r"(obar), "r"(rank ^ 1));
        float o[4][4], t[2][4][4];
#pragma unroll
        for (int j = 0; j < 16; j++) (&o[0][0])[j] = (&t[0][0][0])[j] = (&t[1][0][0])[j] = 0.f;
        const uint32_t voff = (w >> 1) * 8192 + (lane & 15) * 128;
        const int vc = (w & 1) * 4 + (lane >> 4), vx = lane & 7;
        const uint32_t v0 = pin(sb + voff + ((vc ^ vx) << 4)), v1 = pin(sb + voff + (((vc + 2) ^ vx) << 4));
        pkt_store(oout0, 0, 0, 0, 0, tag ^ 1);
        uint32_t p[4][4], b0[4][4], b1[4][4];
        float a0 = 0.f, a1 = 0.f;
        auto load_v = [&](int st) {
#pragma unroll
            for (int j = 0; j < 4; j++) {
                ldsm4t(b0[j], v0 + st * STAGE + j * 2048);
                ldsm4t(b1[j], v1 + st * STAGE + j * 2048);
            }
        };
        auto next_p = [&](int i) {
            const int slot = i % NP;
            mbar_wait(sb + BAR_PFULL + 8 * slot, (i / NP) & 1);
#pragma unroll
            for (int j = 0; j < 4; j++) lds128(p[j], sb + OFF_P + slot * 2048 + j * 512 + lane * 16);
            const float n0 = lds32f(sb + OFF_ALPHA + slot * 64 + g8 * 4), n1 = lds32f(sb + OFF_ALPHA + slot * 64 + 32 + g8 * 4);
            __syncwarp();
            if (lane == 0) mbar_arrive(sb + BAR_PEMPTY + 8 * slot);
#pragma unroll
            for (int j = 0; j < 4; j++) {
                o[j][0] = fmaf(o[j][0], a0, t[0][j][0] + t[1][j][0]); o[j][1] = fmaf(o[j][1], a0, t[0][j][1] + t[1][j][1]);
                o[j][2] = fmaf(o[j][2], a1, t[0][j][2] + t[1][j][2]); o[j][3] = fmaf(o[j][3], a1, t[0][j][3] + t[1][j][3]);
            }
            a0 = n0; a1 = n1;
        };
        auto pv = [&]() {
#pragma unroll
            for (int j = 0; j < 16; j++) (&t[0][0][0])[j] = (&t[1][0][0])[j] = 0.f;
#pragma unroll
            for (int j = 0; j < 4; j++) {
                mma(t[j & 1][0], p[j], b0[j][0], b0[j][1]);
                mma(t[j & 1][1], p[j], b0[j][2], b0[j][3]);
                mma(t[j & 1][2], p[j], b1[j][0], b1[j][1]);
                mma(t[j & 1][3], p[j], b1[j][2], b1[j][3]);
            }
        };
        int st = KA + 1;
        uint32_t par = 0;
#pragma unroll 1
        for (int i = 0; i < NT - 1; i++) {
            mbar_wait(sb + BAR_FULL + 8 * st, par);
            load_v(st);
            next_p(i);
            pv();
            __syncwarp();
            if (lane == 0) mbar_arrive(sb + BAR_EMPTY + 8 * st);
            st += i < NT - KA - 1 ? 2 : 1;
            if (st >= NST) { st -= NST; par ^= 1; }
        }
        constexpr int LST = (2 * NT - 1) % NST, LPAR = ((2 * NT - 1) / NST) & 1;
        const bool landed = mbar_test(sb + BAR_FULL + 8 * LST, LPAR);
        if (landed) load_v(LST);
        next_p(NT - 1);
        mbar_wait(sb + BAR_F, 0);
        const float f0 = lds32f(sb + OFF_F + g8 * 4), f1 = lds32f(sb + OFF_F + 32 + g8 * 4);
        a0 *= f0; a1 *= f1;
#pragma unroll
        for (int j = 0; j < 4; j++) {
            o[j][0] *= a0; o[j][1] *= a0; o[j][2] *= a1; o[j][3] *= a1;
            asm volatile("" : "+f"(o[j][0]), "+f"(o[j][1]), "+f"(o[j][2]), "+f"(o[j][3]));
        }
        if (!landed) {
            mbar_wait(sb + BAR_FULL + 8 * LST, LPAR);
            load_v(LST);
        }
        auto finish = [&]() {
            pv();
#pragma unroll
            for (int j = 0; j < 4; j++) {
                o[j][0] = fmaf(t[0][j][0] + t[1][j][0], f0, o[j][0]); o[j][1] = fmaf(t[0][j][1] + t[1][j][1], f0, o[j][1]);
                o[j][2] = fmaf(t[0][j][2] + t[1][j][2], f1, o[j][2]); o[j][3] = fmaf(t[0][j][3] + t[1][j][3], f1, o[j][3]);
            }
        };
        auto send = [&]() {
#pragma unroll
            for (int k = 0; k < 4; k++) {
                const int e = k < 2 ? 2 : 0, j = (k & 1) * 2;
                asm volatile("st.async.weak.shared::cluster.mbarrier::complete_tx::bytes.v4.f32 [%0], {%1,%2,%3,%4}, [%5];"
                             ::"r"(ra + k * 2048), "f"(o[j][e]), "f"(o[j][e + 1]), "f"(o[j + 1][e]), "f"(o[j + 1][e + 1]),
                               "r"(rbar + (k < 2 ? 0 : 32)) : "memory");
            }
        };
        auto publish = [&](uint4* dst, int e, const float4& r0, const float4& r1) {
            pkt_store(dst, pack_bf16(o[0][e] + r0.x, o[0][e + 1] + r0.y), pack_bf16(o[1][e] + r0.z, o[1][e + 1] + r0.w),
                      pack_bf16(o[2][e] + r1.x, o[2][e + 1] + r1.y), pack_bf16(o[3][e] + r1.z, o[3][e + 1] + r1.w), tag);
        };
        const bool ha = mbar_test(obar, 0), hb = mbar_test(obar + 32, 0);
        if (ha && hb) {
            const float4 r0 = lds128f(la), r1 = lds128f(la + 2048), r2 = lds128f(la + 4096), r3 = lds128f(la + 6144);
            finish();
            publish(oout0, 0, r0, r1);
            publish(oout1, 2, r2, r3);
            send();
        } else {
            finish();
            send();
            mbar_wait(obar, 0);
            const float4 r0 = lds128f(la), r1 = lds128f(la + 2048);
            publish(oout0, 0, r0, r1);
        }
        if (lane == 0) mbar_arrive(sb + BAR_D);
    }

    {
        uint32_t a[8][2][4];
        const int kr = (lane >> 4) * 8 + (lane & 7);
        const int wc = (lane >> 3) & 1, wx = (kr >> 1) & 3;
        const uint32_t wb0 = pin(sb + OFF_WO + (g * 128 + kr) * 64 + ((wc ^ wx) << 4));
        const uint32_t wb1 = pin(sb + OFF_WO + (g * 128 + kr) * 64 + (((wc + 2) ^ wx) << 4));
        const uint32_t red = pin(sb + OFF_PRED + rh * 8192 + lane * 16);
        const uint32_t rw = pin(red + g * 512), rr = pin(red + (g & 1) * 4096 + (g >> 1) * 2048);
        const uint32_t wobar = sb + BAR_WO + 8 * g;
        constexpr uint32_t wopar = 0;
        auto wo_within = [&](uint32_t clks) {
            uint32_t c0, c1;
            bool in;
            asm volatile("mov.u32 %0, %%clock;" : "=r"(c0));
            do {
                in = mbar_test(wobar, wopar);
                asm volatile("mov.u32 %0, %%clock;" : "=r"(c1));
            } while (!in && c1 - c0 < clks);
            return in;
        };
        Pkt v[8];
        const bool in0 = wo_within(O_DELAY);
        pkt_issue<8, 4, 128, 32>(v, oin);
        if (!in0) {
#pragma unroll 1
            for (int it = 0; !wo_within(O_PERIOD); it++) {
                uint32_t b[8];
#pragma unroll
                for (int i = 0; i < 8; i++) b[i] = v[i].bad(tag);
                if (it > (1 << 16)) __trap();
#pragma unroll
                for (int i = 0; i < 8; i++) pkt_reload(v[i], oin + (i >> 2) * 32 + (i & 3) * 128, b[i]);
            }
        }
#pragma unroll
        for (int ks = 0; ks < 8; ks++) {
            ldsm4t(a[ks][0], wb0 + ks * 1024);
            ldsm4t(a[ks][1], wb1 + ks * 1024);
        }
        pkt_poll<8, 4, 128, 32>(v, oin, tag | (a[7][1][3] & zero));
        float c[2][2][2][4];
#pragma unroll
        for (int j = 0; j < 32; j++) (&c[0][0][0][0])[j] = 0.f;
#pragma unroll
        for (int dq = 0; dq < 4; dq++)
#pragma unroll
            for (int t = 0; t < 2; t++) {
                mma(c[t][0][0], a[2 * dq][0], v[t * 4 + dq].w0(), v[t * 4 + dq].w1());
                mma(c[t][1][0], a[2 * dq][1], v[t * 4 + dq].w0(), v[t * 4 + dq].w1());
                mma(c[t][0][1], a[2 * dq + 1][0], v[t * 4 + dq].w2(), v[t * 4 + dq].w3());
                mma(c[t][1][1], a[2 * dq + 1][1], v[t * 4 + dq].w2(), v[t * 4 + dq].w3());
            }
#pragma unroll
        for (int t = 0; t < 2; t++)
#pragma unroll
            for (int mt = 0; mt < 2; mt++)
                sts128f(rw + t * 4096 + mt * 2048, c[t][mt][0][0] + c[t][mt][1][0], c[t][mt][0][1] + c[t][mt][1][1],
                        c[t][mt][0][2] + c[t][mt][1][2], c[t][mt][0][3] + c[t][mt][1][3]);
        bar_sync(3 + rh, 128);
        const float4 s0 = lds128f(rr), s1 = lds128f(rr + 512), s2 = lds128f(rr + 1024), s3 = lds128f(rr + 1536);
        pkt_store(pout, __float_as_uint((s0.x + s1.x) + (s2.x + s3.x)), __float_as_uint((s0.y + s1.y) + (s2.y + s3.y)),
                  __float_as_uint((s0.z + s1.z) + (s2.z + s3.z)), __float_as_uint((s0.w + s1.w) + (s2.w + s3.w)), tag);
    }

    {
        if (warp < 4) {
            Pkt v[2];
            spin(P_DELAY);
            pkt_load(v[0], pin_);
            pkt_load(v[1], pin_ + 128);
#pragma unroll 1
            for (int it = 0;; it++) {
                const uint32_t b0 = v[0].bad(tag), b1 = v[1].bad(tag);
                if (!any_bit0(or3(b0, b1, 0u))) break;
                pkt_reload(v[0], pin_, b0);
                pkt_reload(v[1], pin_ + 128, b1);
                if (it > (1 << 20)) __trap();
            }
            const float e0 = __uint_as_float(v[0].w0()) + __uint_as_float(v[1].w0()), e1 = __uint_as_float(v[0].w1()) + __uint_as_float(v[1].w1());
            const float e2 = __uint_as_float(v[0].w2()) + __uint_as_float(v[1].w2()), e3 = __uint_as_float(v[0].w3()) + __uint_as_float(v[1].w3());
            const bool hi = lane & 8, hi2 = lane & 16;
            const float k0 = (hi ? e1 : e0) + __shfl_xor_sync(0xffffffffu, hi ? e0 : e1, 8);
            const float k1 = (hi ? e3 : e2) + __shfl_xor_sync(0xffffffffu, hi ? e2 : e3, 8);
            const uint32_t res = pack_bf16((hi2 ? k1 : k0) + __shfl_xor_sync(0xffffffffu, hi2 ? k0 : k1, 16), 0.f);
            asm volatile("st.global.u16 [%0], %1;" ::"l"(optr), "h"((uint16_t)res) : "memory");
        }
        if ((cta | warp | lane) == 0)
            asm volatile("st.relaxed.gpu.global.u32 [%0], %1;" ::"l"(&g_scr.epoch), "r"(epoch + 1) : "memory");
        if (warp >= 4) mbar_wait(sb + BAR_G + 8 * (warp - 4), 0);
    }
}

__global__ void fb_proj(const __nv_bfloat16* a_bf, const float* a_f, const __nv_bfloat16* w, int K, int N, float* o_f,
                        __nv_bfloat16* o_bf) {
    const int c = blockIdx.x * blockDim.x + threadIdx.x, r = blockIdx.y;
    float s = 0.f;
    for (int k = 0; k < K; k++) s += (a_bf ? __bfloat162float(a_bf[r * K + k]) : a_f[r * K + k]) * __bfloat162float(w[k * N + c]);
    if (o_bf) o_bf[r * N + c] = __float2bfloat16(s);
    else o_f[r * N + c] = __bfloat162float(__float2bfloat16(s));
}
__global__ void fb_attn(const __nv_bfloat16* kc, const __nv_bfloat16* vc) {
    __shared__ float sc[2048], red[128];
    const int r = blockIdx.x, hq = blockIdx.y, t = threadIdx.x;
    const size_t base = (size_t)((r >> 2) * 8 + (hq >> 2)) * 2048 * 128;
    float m = -INFINITY, l = 0.f, acc = 0.f;
    for (int j = t; j < 2048; j += 128) {
        float s = 0.f;
        for (int d = 0; d < 128; d++) s += g_scr.fq[r * 4096 + hq * 128 + d] * __bfloat162float(kc[base + j * 128 + d]);
        sc[j] = s * 0.08838834764831845f;
        m = fmaxf(m, sc[j]);
    }
    red[t] = m;
    __syncthreads();
    for (int i = 0; i < 128; i++) m = fmaxf(m, red[i]);
    for (int j = t; j < 2048; j += 128) sc[j] = __expf(sc[j] - m);
    __syncthreads();
    for (int j = 0; j < 2048; j++) {
        l += sc[j];
        acc += sc[j] * __bfloat162float(vc[base + j * 128 + t]);
    }
    g_scr.fo[r * 4096 + hq * 128 + t] = __bfloat162float(__float2bfloat16(acc / l));
}

typedef CUresult (*EncodeFn)(CUtensorMap*, CUtensorMapDataType, cuuint32_t, void*, const cuuint64_t*, const cuuint64_t*,
                             const cuuint32_t*, const cuuint32_t*, CUtensorMapInterleave, CUtensorMapSwizzle,
                             CUtensorMapL2promotion, CUtensorMapFloatOOBfill);

static void encode(EncodeFn fn, CUtensorMap* m, void* p, int rank, const cuuint64_t* dims, const cuuint64_t* strides,
                   const cuuint32_t* box, CUtensorMapSwizzle sw) {
    const cuuint32_t es[3] = {1, 1, 1};
    fn(m, CU_TENSOR_MAP_DATA_TYPE_BFLOAT16, rank, p, dims, strides, box, es, CU_TENSOR_MAP_INTERLEAVE_NONE, sw,
       CU_TENSOR_MAP_L2_PROMOTION_L2_256B, CU_TENSOR_MAP_FLOAT_OOB_FILL_NONE);
}

}

extern "C" void kernel_launch(void* const* d_in, const int* in_sizes, int n_in, void* d_out, int out_size) {
    using namespace gqa;
    static EncodeFn fn = nullptr;
    static uint32_t slot_ns = SLOT_NS;
    static bool fits = false;
    if (!fn) {
        int dev = 0, khz = 0, bits = 0;
        cudaGetDevice(&dev);
        cudaDeviceGetAttribute(&khz, cudaDevAttrMemoryClockRate, dev);
        cudaDeviceGetAttribute(&bits, cudaDevAttrGlobalMemoryBusWidth, dev);
        if (khz > 0 && bits > 0) slot_ns = (uint32_t)((double)NCTA * STAGE / (0.955 * 2.0 * khz * 1e-6 * (bits / 8)));
        void* p = nullptr;
        cudaDriverEntryPointQueryResult qr;
        cudaGetDriverEntryPoint("cuTensorMapEncodeTiled", &p, cudaEnableDefault, &qr);
        fn = (EncodeFn)p;
        cudaFuncSetAttribute(gqa_kernel, cudaFuncAttributeMaxDynamicSharedMemorySize, SMEM_BYTES);
        cudaLaunchConfig_t cfg = {};
        cfg.gridDim = dim3(NCTA);
        cfg.blockDim = dim3(288);
        cfg.dynamicSmemBytes = SMEM_BYTES;
        int clusters = 0;
        fits = cudaOccupancyMaxActiveClusters(&clusters, gqa_kernel, &cfg) == cudaSuccess && clusters >= NCTA / 2;
    }
    if (!fits) {
        Scratch* scr = nullptr;
        cudaGetSymbolAddress((void**)&scr, g_scr);
        float *fq = scr->fq, *fo = scr->fo;
        fb_proj<<<dim3(16, 32), 256, 0, cudaStreamPerThread>>>((const __nv_bfloat16*)d_in[0], nullptr, (const __nv_bfloat16*)d_in[3], 512,
                                                               4096, fq, nullptr);
        fb_attn<<<dim3(32, 32), 128, 0, cudaStreamPerThread>>>((const __nv_bfloat16*)d_in[1], (const __nv_bfloat16*)d_in[2]);
        fb_proj<<<dim3(2, 32), 256, 0, cudaStreamPerThread>>>(nullptr, fo, (const __nv_bfloat16*)d_in[4], 4096, 512, nullptr,
                                                              (__nv_bfloat16*)d_out);
        return;
    }
    CUtensorMap tmK, tmV, tmX, tmWq, tmWo;
    {
        const cuuint64_t dims[3] = {64, 8 * 8 * 2048, 2}, str[2] = {256, 128};
        const cuuint32_t box[3] = {64, 64, 2};
        encode(fn, &tmK, d_in[1], 3, dims, str, box, CU_TENSOR_MAP_SWIZZLE_128B);
        encode(fn, &tmV, d_in[2], 3, dims, str, box, CU_TENSOR_MAP_SWIZZLE_128B);
    }
    {
        const cuuint64_t dims[3] = {64, 32, 8}, str[2] = {1024, 128};
        const cuuint32_t box[3] = {64, 32, 8};
        encode(fn, &tmX, d_in[0], 3, dims, str, box, CU_TENSOR_MAP_SWIZZLE_128B);
    }
    {
        const cuuint64_t dq[2] = {4096, 512}, sq[1] = {8192}, dw[2] = {512, 4096}, sw[1] = {1024};
        const cuuint32_t box[2] = {32, 256};
        encode(fn, &tmWq, d_in[3], 2, dq, sq, box, CU_TENSOR_MAP_SWIZZLE_64B);
        const cuuint32_t boxo[2] = {32, 128};
        encode(fn, &tmWo, d_in[4], 2, dw, sw, boxo, CU_TENSOR_MAP_SWIZZLE_64B);
    }
    gqa_kernel<<<NCTA, 288, SMEM_BYTES, cudaStreamPerThread>>>(Ptrs{{(const uint8_t*)d_in[3], nullptr}}, (__nv_bfloat16*)d_out, slot_ns, 0u, tmK, tmV, tmX,
                                                               tmWq, tmWo);
}
```

```cpp
#include <cuda_runtime.h>
#include <cuda_bf16.h>
#include <cuda.h>
#include <stdint.h>

namespace gqa {

constexpr int PA_NS = 2780;
constexpr int SLOT_NS = 655;
constexpr int WO_SLOT = 2895;
constexpr int WO_STEP = 65;
constexpr int Q_DELAY_NS = 1000;
constexpr int O_DELAY = 900;
constexpr int O_PERIOD = 350;
constexpr int P_DELAY = 330;
constexpr int PF_BYTES = 8192;

constexpr int NCTA = 128;
constexpr int NT = 16;
constexpr int NST = 13;
constexpr int NST0 = 10;
constexpr int WIN0 = 3;
constexpr int WIN = 8;
constexpr int WSW = 8;
constexpr int KA = 2;
constexpr int NP = 4;
constexpr int STAGE = 16384;

constexpr int OFF_WQ = NST0 * STAGE;
constexpr int OFF_X = OFF_WQ + 32768;
constexpr int OFF_QRED = OFF_X;
constexpr int OFF_WO = ((2 * NT) % NST) * STAGE;
constexpr int OFF_P = NST * STAGE;
constexpr int OFF_MERGE = (((2 * NT) % NST) + 3) * STAGE;
constexpr int OFF_ALPHA = (NST + 1) * STAGE + 512;
constexpr int OFF_WMAX = OFF_ALPHA + 2 * NP * 64;
constexpr int OFF_LSUM = OFF_WMAX + 512;
constexpr int OFF_MROW = OFF_LSUM + 256;
constexpr int OFF_STAT = OFF_MROW + 64;
constexpr int OFF_F = OFF_STAT + 128;
constexpr int OFF_PRED = (((2 * NT) % NST) + 2) * STAGE;
constexpr int OFF_BAR = (NST + 1) * STAGE;
constexpr int BAR_FULL = OFF_BAR;
constexpr int BAR_EMPTY = BAR_FULL + 8 * NST;
constexpr int BAR_PFULL = BAR_EMPTY + 8 * NST;
constexpr int BAR_PEMPTY = BAR_PFULL + 16 * NP;
constexpr int BAR_W = BAR_PEMPTY + 16 * NP;
constexpr int BAR_STAT = BAR_W + 8;
constexpr int BAR_F = BAR_STAT + 8;
constexpr int BAR_D = BAR_F + 8;
constexpr int BAR_WO = BAR_D + 8;
constexpr int SMEM_BYTES = OFF_F + 128;
static_assert(2 * NP * 2048 <= STAGE, "P slots overflow");
static_assert(BAR_WO + 32 <= OFF_ALPHA, "barriers overflow");
static_assert((2 * NT) % NST + 3 < NST, "wo / partial slots must not wrap");
static_assert(SMEM_BYTES <= 232448, "too much shared memory");

struct __align__(1024) Scratch {
    uint4 q[32 * 4 * 8 * 16];
    uint4 o[32 * 4 * 8 * 16];
    uint4 p[128 * 8 * 32];
    unsigned epoch;
    float fq[32 * 4096], fo[32 * 4096];
};
__device__ Scratch g_scr;

__device__ __forceinline__ void mbar_init(uint32_t bar, uint32_t cnt) {
    asm volatile("mbarrier.init.shared::cta.b64 [%0], %1;" ::"r"(bar), "r"(cnt) : "memory");
}
__device__ __forceinline__ void mbar_expect_tx(uint32_t bar, uint32_t bytes) {
    asm volatile("mbarrier.arrive.expect_tx.shared::cta.b64 _, [%0], %1;" ::"r"(bar), "r"(bytes) : "memory");
}
__device__ __forceinline__ void mbar_arrive(uint32_t bar) {
    asm volatile("mbarrier.arrive.shared::cta.b64 _, [%0];" ::"r"(bar) : "memory");
}
__device__ __forceinline__ bool mbar_try(uint32_t bar, uint32_t parity) {
    uint32_t ok;
    asm volatile("{\n.reg .pred p;\nmbarrier.try_wait.parity.shared::cta.b64 p, [%1], %2;\nselp.u32 %0, 1, 0, p;\n}"
                 : "=r"(ok) : "r"(bar), "r"(parity) : "memory");
    return ok;
}
__device__ __forceinline__ bool mbar_test(uint32_t bar, uint32_t parity) {
    uint32_t ok;
    asm volatile("{\n.reg .pred p;\nmbarrier.test_wait.parity.shared::cta.b64 p, [%1], %2;\nselp.u32 %0, 1, 0, p;\n}"
                 : "=r"(ok) : "r"(bar), "r"(parity) : "memory");
    return ok;
}
__device__ __forceinline__ void mbar_wait(uint32_t bar, uint32_t parity) {
#pragma unroll 1
    for (int i = 0; !mbar_try(bar, parity); i++)
        if (i > (1 << 20)) __trap();
}
__device__ __forceinline__ void tma2d(uint32_t dst, const CUtensorMap* m, int c0, int c1, uint32_t bar) {
    asm volatile("cp.async.bulk.tensor.2d.shared::cluster.global.mbarrier::complete_tx::bytes [%0], [%1, {%3, %4}], [%2];"
                 ::"r"(dst), "l"(m), "r"(bar), "r"(c0), "r"(c1) : "memory");
}
__device__ __forceinline__ void tma3d(uint32_t dst, const CUtensorMap* m, int c0, int c1, int c2, uint32_t bar) {
    asm volatile("cp.async.bulk.tensor.3d.shared::cluster.global.mbarrier::complete_tx::bytes [%0], [%1, {%3, %4, %5}], [%2];"
                 ::"r"(dst), "l"(m), "r"(bar), "r"(c0), "r"(c1), "r"(c2) : "memory");
}
__device__ __forceinline__ void tma2d_hint(uint32_t dst, const CUtensorMap* m, int c0, int c1, uint32_t bar, uint64_t pol) {
    asm volatile("cp.async.bulk.tensor.2d.shared::cluster.global.mbarrier::complete_tx::bytes.L2::cache_hint [%0], [%1, {%3, %4}], [%2], %5;"
                 ::"r"(dst), "l"(m), "r"(bar), "r"(c0), "r"(c1), "l"(pol) : "memory");
}
__device__ __forceinline__ uint32_t mapa(uint32_t addr, uint32_t cta_rank) {
    uint32_t r;
    asm("mapa.shared::cluster.u32 %0, %1, %2;" : "=r"(r) : "r"(addr), "r"(cta_rank));
    return r;
}
__device__ __forceinline__ void tma3d_hint(uint32_t dst, const CUtensorMap* m, int c0, int c1, int c2, uint32_t bar, uint64_t pol) {
    asm volatile("cp.async.bulk.tensor.3d.shared::cluster.global.mbarrier::complete_tx::bytes.L2::cache_hint [%0], [%1, {%3, %4, %5}], [%2], %6;"
                 ::"r"(dst), "l"(m), "r"(bar), "r"(c0), "r"(c1), "r"(c2), "l"(pol) : "memory");
}
__device__ __forceinline__ void ldsm4(uint32_t (&r)[4], uint32_t addr) {
    asm volatile("ldmatrix.sync.aligned.m8n8.x4.shared.b16 {%0,%1,%2,%3}, [%4];"
                 : "=r"(r[0]), "=r"(r[1]), "=r"(r[2]), "=r"(r[3]) : "r"(addr) : "memory");
}
__device__ __forceinline__ void ldsm4t(uint32_t (&r)[4], uint32_t addr) {
    asm volatile("ldmatrix.sync.aligned.m8n8.x4.trans.shared.b16 {%0,%1,%2,%3}, [%4];"
                 : "=r"(r[0]), "=r"(r[1]), "=r"(r[2]), "=r"(r[3]) : "r"(addr) : "memory");
}
__device__ __forceinline__ void mma(float (&c)[4], const uint32_t (&a)[4], uint32_t b0, uint32_t b1) {
    asm volatile("mma.sync.aligned.m16n8k16.row.col.f32.bf16.bf16.f32 {%0,%1,%2,%3}, {%4,%5,%6,%7}, {%8,%9}, {%0,%1,%2,%3};"
                 : "+f"(c[0]), "+f"(c[1]), "+f"(c[2]), "+f"(c[3])
                 : "r"(a[0]), "r"(a[1]), "r"(a[2]), "r"(a[3]), "r"(b0), "r"(b1));
}
__device__ __forceinline__ uint32_t pack_bf16(float lo, float hi) {
    uint32_t r;
    asm("cvt.rn.bf16x2.f32 %0, %1, %2;" : "=r"(r) : "f"(hi), "f"(lo));
    return r;
}
__device__ __forceinline__ float ex2(float x) {
    float y;
    asm("ex2.approx.ftz.f32 %0, %1;" : "=f"(y) : "f"(x));
    return y;
}
__device__ __forceinline__ void sts128(uint32_t addr, uint32_t a, uint32_t b, uint32_t c, uint32_t d) {
    asm volatile("st.shared.v4.b32 [%0], {%1,%2,%3,%4};" ::"r"(addr), "r"(a), "r"(b), "r"(c), "r"(d) : "memory");
}
__device__ __forceinline__ void sts128f(uint32_t addr, float a, float b, float c, float d) {
    asm volatile("st.shared.v4.f32 [%0], {%1,%2,%3,%4};" ::"r"(addr), "f"(a), "f"(b), "f"(c), "f"(d) : "memory");
}
__device__ __forceinline__ void sts32f(uint32_t addr, float a) {
    asm volatile("st.shared.f32 [%0], %1;" ::"r"(addr), "f"(a) : "memory");
}
__device__ __forceinline__ void lds128(uint32_t (&r)[4], uint32_t addr) {
    asm volatile("ld.shared.v4.b32 {%0,%1,%2,%3}, [%4];" : "=r"(r[0]), "=r"(r[1]), "=r"(r[2]), "=r"(r[3]) : "r"(addr) : "memory");
}
__device__ __forceinline__ float4 lds128f(uint32_t addr) {
    float4 v;
    asm volatile("ld.shared.v4.f32 {%0,%1,%2,%3}, [%4];" : "=f"(v.x), "=f"(v.y), "=f"(v.z), "=f"(v.w) : "r"(addr) : "memory");
    return v;
}
__device__ __forceinline__ float lds32f(uint32_t addr) {
    float v;
    asm volatile("ld.shared.f32 %0, [%1];" : "=f"(v) : "r"(addr) : "memory");
    return v;
}
__device__ __forceinline__ void bar_sync(int id, int n) { asm volatile("bar.sync %0, %1;" ::"r"(id), "r"(n) : "memory"); }
template <typename T> __device__ __forceinline__ T* pin(T* p) { asm volatile("" : "+l"(p)); return p; }
__device__ __forceinline__ uint32_t pin(uint32_t v) { asm volatile("" : "+r"(v)); return v; }

struct Pkt {
    uint64_t lo, hi;
    __device__ __forceinline__ uint32_t w0() const { return (uint32_t)lo; }
    __device__ __forceinline__ uint32_t w1() const { return (uint32_t)(lo >> 32); }
    __device__ __forceinline__ uint32_t w2() const { return (uint32_t)hi; }
    __device__ __forceinline__ uint32_t w3() const { return (uint32_t)(hi >> 32); }
    __device__ __forceinline__ uint32_t bad(uint32_t tag) const {
        uint32_t r;
        asm("lop3.b32 %0, %1, %2, %3, 0x7E;" : "=r"(r) : "r"(w0()), "r"(w2()), "r"(tag));
        return r;
    }
};
__device__ __forceinline__ void pkt_store(uint4* p, uint32_t a, uint32_t b, uint32_t c, uint32_t d, uint32_t tag) {
    a = (a & ~1u) | tag;
    c = (c & ~1u) | tag;
    asm volatile("{\n.reg .b64 lo, hi;\nmov.b64 lo, {%1,%2};\nmov.b64 hi, {%3,%4};\n"
                 "st.relaxed.gpu.global.v2.b64 [%0], {lo, hi};\n}" ::"l"(p), "r"(a), "r"(b), "r"(c), "r"(d) : "memory");
}
__device__ __forceinline__ void pkt_load(Pkt& v, const uint4* p) {
    asm volatile("ld.relaxed.gpu.global.v2.b64 {%0, %1}, [%2];" : "=l"(v.lo), "=l"(v.hi) : "l"(p) : "memory");
}
__device__ __forceinline__ void pkt_reload(Pkt& v, const uint4* p, uint32_t bad) {
    asm volatile("{\n.reg .pred p;\n.reg .b32 t;\nand.b32 t, %3, 1;\nsetp.ne.u32 p, t, 0;\n"
                 "@p ld.relaxed.gpu.global.v2.b64 {%0, %1}, [%2];\n}"
                 : "+l"(v.lo), "+l"(v.hi) : "l"(p), "r"(bad) : "memory");
}
__device__ __forceinline__ uint32_t or3(uint32_t a, uint32_t b, uint32_t c) {
    uint32_t r;
    asm("lop3.b32 %0, %1, %2, %3, 0xFE;" : "=r"(r) : "r"(a), "r"(b), "r"(c));
    return r;
}
__device__ __forceinline__ bool any_bit0(uint32_t x) {
    uint32_t r;
    asm volatile("{\n.reg .pred p, q;\n.reg .b32 t;\nand.b32 t, %1, 1;\nsetp.ne.u32 p, t, 0;\nvote.sync.any.pred q, p, 0xffffffff;\n"
                 "selp.u32 %0, 1, 0, q;\n}" : "=r"(r) : "r"(x));
    return r;
}
template <int N, int N0, int S0, int S1>
__device__ __forceinline__ void pkt_issue(Pkt (&v)[N], const uint4* p) {
#pragma unroll
    for (int i = 0; i < N; i++) pkt_load(v[i], p + (i / N0) * S1 + (i % N0) * S0);
}
template <int N, int N0, int S0, int S1>
__device__ __forceinline__ void pkt_poll(Pkt (&v)[N], const uint4* p, uint32_t tag) {
    static_assert(N == 1 || N == 8, "");
#pragma unroll 1
    for (int it = 0;; it++) {
        uint32_t b[N];
#pragma unroll
        for (int i = 0; i < N; i++) b[i] = v[i].bad(tag);
        uint32_t bad = b[0];
        if (N == 8) bad = or3(or3(b[0], b[1 % N], b[2 % N]), or3(b[3 % N], b[4 % N], b[5 % N]), or3(b[6 % N], b[7 % N], 0u));
        if (!any_bit0(bad)) break;
#pragma unroll
        for (int i = 0; i < N; i++) pkt_reload(v[i], p + (i / N0) * S1 + (i % N0) * S0, b[i]);
        if (it > (1 << 20)) __trap();
    }
}

__device__ __forceinline__ uint32_t now_ns() {
    uint32_t t;
    asm volatile("mov.u32 %0, %%globaltimer_lo;" : "=r"(t));
    return t;
}
__device__ __forceinline__ void spin(uint32_t clks) {
    uint32_t c0, c1;
    asm volatile("mov.u32 %0, %%clock;" : "=r"(c0));
    do { asm volatile("mov.u32 %0, %%clock;" : "=r"(c1)); } while (c1 - c0 < clks);
}
__device__ __forceinline__ void wait_until(uint32_t t) {
#pragma unroll 1
    for (int i = 0; (int)(now_ns() - t) < 0 && i < (1 << 16); i++) {}
}

struct Ptrs { const uint8_t* p[2]; };

__global__ void __cluster_dims__(2, 1, 1) __launch_bounds__(288, 1)
gqa_kernel(const __grid_constant__ Ptrs ptrs, __nv_bfloat16* __restrict__ out, uint32_t slot_ns, uint32_t zero,
           const __grid_constant__ CUtensorMap tmK, const __grid_constant__ CUtensorMap tmV,
           const __grid_constant__ CUtensorMap tmX, const __grid_constant__ CUtensorMap tmWq,
           const __grid_constant__ CUtensorMap tmWo) {
    const uint32_t tstart = now_ns();
    if (threadIdx.x == 32)
        asm volatile("cp.async.bulk.prefetch.L2.global [%0], %1;" ::"l"(ptrs.p[blockIdx.x >> 10] + blockIdx.x * PF_BYTES), "r"(PF_BYTES)
                     : "memory");
    extern __shared__ __align__(1024) uint8_t smem_raw[];
    const uint32_t sb = pin((uint32_t)__cvta_generic_to_shared(smem_raw));
    if (threadIdx.x == 0) {
        mbar_init(sb + BAR_W, 1);
        asm volatile("fence.mbarrier_init.release.cluster;" ::: "memory");
        mbar_expect_tx(sb + BAR_W, 65536);
        tma2d(sb + OFF_WQ, &tmWq, blockIdx.x * 32, 0, sb + BAR_W);
        tma2d(sb + OFF_WQ + 16384, &tmWq, blockIdx.x * 32, 256, sb + BAR_W);
        tma3d(sb + OFF_X, &tmX, 0, 0, 0, sb + BAR_W);
    }
    const int warp = __shfl_sync(0xffffffffu, threadIdx.x >> 5, 0), lane = pin(threadIdx.x & 31);
    const int cta = pin(blockIdx.x), rank = cta & 1, bh = cta >> 1;

    if (warp == 8) {
        const int row0 = bh * 2048 + rank * 64;
        uint64_t pol;
        asm volatile("createpolicy.fractional.L2::evict_first.b64 %0, 1.0;" : "=l"(pol));
        auto issue = [&](int n) {
            const bool isv = n >= 2 * NT - KA || (n >= KA && ((n - KA) & 1));
            const int t = n < KA ? n : n >= 2 * NT - KA ? n - NT : isv ? (n - KA) >> 1 : (n + KA) >> 1;
            const int st = n % NST;
            if (isv) tma2d_hint(sb + st * STAGE, &tmV, rank * 64, bh * 2048 + t * 128, sb + BAR_FULL + 8 * st, pol);
            else tma3d_hint(sb + st * STAGE, &tmK, 0, row0 + t * 128, 0, sb + BAR_FULL + 8 * st, pol);
        };
        if (lane == 0) {
            if (sb & 1023) __trap();
#pragma unroll
            for (int i = 0; i < WIN0; i++) mbar_init(sb + BAR_FULL + 8 * i, 1);
            asm volatile("fence.mbarrier_init.release.cluster;" ::: "memory");
#pragma unroll
            for (int n = 0; n < WIN0; n++) {
                mbar_expect_tx(sb + BAR_FULL + 8 * n, STAGE);
                issue(n);
            }
            for (int i = WIN0; i < NST; i++) mbar_init(sb + BAR_FULL + 8 * i, 1);
            for (int i = 0; i < NST; i++) mbar_init(sb + BAR_EMPTY + 8 * i, 4);
            for (int i = 0; i < NP; i++) {
                mbar_init(sb + BAR_PFULL + 8 * i, 4);
                mbar_init(sb + BAR_PFULL + 8 * (NP + i), 1);
                mbar_expect_tx(sb + BAR_PFULL + 8 * (NP + i), 2048 + 64);
                mbar_init(sb + BAR_PEMPTY + 8 * i, 2);
                mbar_init(sb + BAR_PEMPTY + 8 * (NP + i), 2);
            }
            mbar_init(sb + BAR_STAT, 1);
            mbar_init(sb + BAR_F, 1);
            mbar_init(sb + BAR_D, 4);
            mbar_expect_tx(sb + BAR_STAT, 128);
            for (int i = 0; i < 4; i++) {
                mbar_init(sb + BAR_WO + 8 * i, 1);
                mbar_expect_tx(sb + BAR_WO + 8 * i, 8192);
            }
            asm volatile("fence.mbarrier_init.release.cluster;" ::: "memory");
            asm volatile("prefetch.tensormap [%0];" ::"l"(&tmWo) : "memory");
        }
        __syncthreads();
        asm volatile("barrier.cluster.arrive.relaxed.aligned;" ::: "memory");
        if (lane == 0) {
            auto wait_free = [&](int n) {
                const int st = n % NST, k = n / NST;
                if (st >= NST0) mbar_wait(sb + BAR_EMPTY + 8 * st, k & 1);
                else if (k) mbar_wait(sb + BAR_EMPTY + 8 * st, (k - 1) & 1);
            };
            const uint32_t t3 = tstart + PA_NS;
#pragma unroll
            for (int n = WIN0; n < 2 * NT; n++) {
                wait_free(n);
                mbar_expect_tx(sb + BAR_FULL + 8 * (n % NST), STAGE);
                if (n < WSW || n >= WSW + WIN - WIN0) {
                    const int d = n - (n < WSW ? WIN0 : WIN);
                    mbar_wait(sb + BAR_FULL + 8 * (d % NST), (d / NST) & 1);
                }
                if (n >= WSW) wait_until(t3 + (n - 3) * slot_ns);
                issue(n);
            }
            wait_free(2 * NT); wait_free(2 * NT + 1); wait_free(2 * NT + 2);
#pragma unroll
            for (int g = 0; g < 4; g++) {
                wait_until(t3 + (WO_SLOT + g * WO_STEP) * slot_ns / 100);
                tma2d(sb + OFF_WO + g * 8192, &tmWo, (cta & 15) * 32, (cta >> 4) * 512 + g * 128, sb + BAR_WO + 8 * g);
            }
        }
        return;
    }

    unsigned epoch;
    asm volatile("ld.relaxed.gpu.global.u32 %0, [%1];" : "=r"(epoch) : "l"(&g_scr.epoch) : "memory");
    const int g8 = lane >> 2, quad = lane & 3;
    const int rh = warp >> 2, g = (warp + 2 * rh) & 3;
    const uint4* const oin = pin(&g_scr.o[((cta >> 4) * 4 + g) * 512 + rh * 64 + lane]);
    uint4* const pout = pin(&g_scr.p[(((rh * 2 + (g & 1)) * 32 + (cta & 15) * 2 + (g >> 1)) * 8 + (cta >> 4)) * 32 + quad * 8 + g8]);
    const uint4* const pin_ = pin(&g_scr.p[(cta * 8 + (lane >> 3)) * 32 + (warp & 3) * 8 + (lane & 7)]);
    __nv_bfloat16* const optr = pin(out + ((cta >> 5) * 8 + (warp & 3) * 2 + ((lane >> 3) & 1)) * 512 + (cta & 31) * 16 + (lane & 7) +
                                    (lane >> 4) * 8);
    __syncthreads();

    {
        const int kq = warp & 3, mt = warp >> 2;
        float c[4][4];
#pragma unroll
        for (int j = 0; j < 4; j++) c[j][0] = c[j][1] = c[j][2] = c[j][3] = 0.f;
        const int ar = mt * 16 + (lane & 15);
        const uint32_t abase = sb + OFF_X + kq * 8192 + ar * 128;
        const int br = lane & 15;
        const uint32_t bbase = sb + OFF_WQ + (kq * 128 + br) * 64;
        if (warp < 4) pkt_store(&g_scr.q[cta * 128 + warp * 32 + lane], 0, 0, 0, 0, epoch & 1);
        pkt_store(pout, 0, 0, 0, 0, epoch & 1);
        mbar_wait(sb + BAR_W, 0);
#pragma unroll
        for (int ks = 0; ks < 8; ks++) {
            uint32_t a[4], b0[4], b1[4];
            ldsm4(a, abase + (ks >> 2) * 4096 + ((((ks & 3) * 2 + (lane >> 4)) ^ (ar & 7)) << 4));
            ldsm4t(b0, bbase + ks * 1024 + (((lane >> 4) ^ ((br >> 1) & 3)) << 4));
            ldsm4t(b1, bbase + ks * 1024 + (((2 + (lane >> 4)) ^ ((br >> 1) & 3)) << 4));
            mma(c[0], a, b0[0], b0[1]);
            mma(c[1], a, b0[2], b0[3]);
            mma(c[2], a, b1[0], b1[1]);
            mma(c[3], a, b1[2], b1[3]);
        }
        bar_sync(1, 256);
        asm volatile("barrier.cluster.arrive.relaxed.aligned;" ::: "memory");
        const uint32_t rb = sb + OFF_QRED + (kq * 2 + mt) * 2048 + lane * 16;
        sts128f(rb, c[0][0], c[0][1], c[1][0], c[1][1]);
        sts128f(rb + 512, c[2][0], c[2][1], c[3][0], c[3][1]);
        sts128f(rb + 1024, c[0][2], c[0][3], c[1][2], c[1][3]);
        sts128f(rb + 1536, c[2][2], c[2][3], c[3][2], c[3][3]);
        bar_sync(1, 256);
    }
    const uint32_t tag = pin((epoch + 1) & 1);

    if (warp < 4) {
        {
            const uint32_t rb = sb + OFF_QRED + warp * 1024 + lane * 16;
            float4 s0 = lds128f(rb), s1 = lds128f(rb + 512);
#pragma unroll
            for (int kq = 1; kq < 4; kq++) {
                float4 t0 = lds128f(rb + kq * 4096), t1 = lds128f(rb + kq * 4096 + 512);
                s0.x += t0.x; s0.y += t0.y; s0.z += t0.z; s0.w += t0.w;
                s1.x += t1.x; s1.y += t1.y; s1.z += t1.z; s1.w += t1.w;
            }
            pkt_store(&g_scr.q[cta * 128 + warp * 32 + lane], pack_bf16(s0.x, s0.y), pack_bf16(s0.z, s0.w),
                      pack_bf16(s1.x, s1.y), pack_bf16(s1.z, s1.w), tag);
            __syncwarp();
            if (lane < NST - NST0) mbar_arrive(sb + BAR_EMPTY + 8 * (NST0 + lane));
        }
        __nanosleep(Q_DELAY_NS);
        uint32_t q[8][4];
        {
            Pkt v[8];
            const uint4* qp = &g_scr.q[(((bh & 7) * 4 + (lane >> 4)) * 4) * 128 + (bh >> 3) * 16 + (lane & 15)];
            pkt_issue<8, 4, 128, 1024>(v, qp);
            pkt_poll<8, 4, 128, 1024>(v, qp, tag);
#pragma unroll
            for (int dq = 0; dq < 4; dq++) {
                const Pkt &a = v[dq], &b = v[4 + dq];
                q[2 * dq][0] = a.w0();     q[2 * dq][1] = b.w0();     q[2 * dq][2] = a.w1();     q[2 * dq][3] = b.w1();
                q[2 * dq + 1][0] = a.w2(); q[2 * dq + 1][1] = b.w2(); q[2 * dq + 1][2] = a.w3(); q[2 * dq + 1][3] = b.w3();
            }
        }
        asm volatile("barrier.cluster.wait.acquire.aligned;" ::: "memory");
        constexpr float C = 0.08838834764831845f * 1.4426950408889634f;
        float mc0 = -INFINITY, mc1 = -INFINITY, l0 = 0.f, l1 = 0.f;
        const int key = warp * 16 + (lane >> 4) * 8 + (lane & 7);
        const uint32_t koff = key * 128;
        const int ksel = (lane >> 3) & 1, kx = lane & 7;
        const uint32_t rp = mapa(sb + OFF_P + NP * 2048 + warp * 512 + lane * 16, rank ^ 1);
        const uint32_t ra = mapa(sb + OFF_ALPHA + NP * 64 + g8 * 4, rank ^ 1), rfull = mapa(sb + BAR_PFULL + 8 * NP, rank ^ 1);
        int st = 0;
        uint32_t par = 0;
#pragma unroll 1
        for (int i = 0; i < NT; i++) {
            const uint32_t kb = sb + st * STAGE + koff;
            float s[2][2][4];
#pragma unroll
            for (int j = 0; j < 4; j++) s[0][0][j] = s[0][1][j] = s[1][0][j] = s[1][1][j] = 0.f;
            mbar_wait(sb + BAR_FULL + 8 * st, par);
#pragma unroll
            for (int ks = 0; ks < 8; ks++) {
                uint32_t b[4];
                ldsm4(b, kb + (ks >> 2) * 8192 + ((((ks & 3) * 2 + ksel) ^ kx) << 4));
                mma(s[ks & 1][0], q[ks], b[0], b[1]);
                mma(s[ks & 1][1], q[ks], b[2], b[3]);
            }
            __syncwarp();
            if (lane == 0) mbar_arrive(sb + BAR_EMPTY + 8 * st);
            st += i < KA ? 1 : 2;
            if (st >= NST) { st -= NST; par ^= 1; }
            float sv[2][4];
#pragma unroll
            for (int j = 0; j < 4; j++) { sv[0][j] = s[0][0][j] + s[1][0][j]; sv[1][j] = s[0][1][j] + s[1][1][j]; }
            float t0 = fmaxf(fmaxf(sv[0][0], sv[0][1]), fmaxf(sv[1][0], sv[1][1]));
            float t1 = fmaxf(fmaxf(sv[0][2], sv[0][3]), fmaxf(sv[1][2], sv[1][3]));
            t0 = fmaxf(t0, __shfl_xor_sync(0xffffffffu, t0, 1));
            t1 = fmaxf(t1, __shfl_xor_sync(0xffffffffu, t1, 1));
            t0 = fmaxf(t0, __shfl_xor_sync(0xffffffffu, t0, 2));
            t1 = fmaxf(t1, __shfl_xor_sync(0xffffffffu, t1, 2));
            const uint32_t wm = sb + OFF_WMAX + (i & 1) * 256 + g8 * 16;
            if (quad == 0) { sts32f(wm + warp * 4, t0); sts32f(wm + 128 + warp * 4, t1); }
            bar_sync(2, 128);
            const float4 w0 = lds128f(wm), w1 = lds128f(wm + 128);
            const float n0 = fmaxf(mc0, fmaxf(fmaxf(w0.x, w0.y), fmaxf(w0.z, w0.w)) * C);
            const float n1 = fmaxf(mc1, fmaxf(fmaxf(w1.x, w1.y), fmaxf(w1.z, w1.w)) * C);
            const float a0 = ex2(mc0 - n0), a1 = ex2(mc1 - n1);
            mc0 = n0; mc1 = n1;
            float p[2][4];
#pragma unroll
            for (int j = 0; j < 2; j++) {
                p[j][0] = ex2(fmaf(sv[j][0], C, -n0)); p[j][1] = ex2(fmaf(sv[j][1], C, -n0));
                p[j][2] = ex2(fmaf(sv[j][2], C, -n1)); p[j][3] = ex2(fmaf(sv[j][3], C, -n1));
            }
            l0 = l0 * a0 + ((p[0][0] + p[0][1]) + (p[1][0] + p[1][1]));
            l1 = l1 * a1 + ((p[0][2] + p[0][3]) + (p[1][2] + p[1][3]));
            const int slot = i % NP;
            if (i >= NP) {
                mbar_wait(sb + BAR_PEMPTY + 8 * slot, (i / NP - 1) & 1);
                mbar_wait(sb + BAR_PEMPTY + 8 * (NP + slot), (i / NP - 1) & 1);
            }
            const uint32_t p0 = pack_bf16(p[0][0], p[0][1]), p1 = pack_bf16(p[0][2], p[0][3]), p2 = pack_bf16(p[1][0], p[1][1]),
                           p3 = pack_bf16(p[1][2], p[1][3]);
            asm volatile("st.async.weak.shared::cluster.mbarrier::complete_tx::bytes.v4.b32 [%0], {%1,%2,%3,%4}, [%5];"
                         ::"r"(rp + slot * 2048), "r"(p0), "r"(p1), "r"(p2), "r"(p3), "r"(rfull + 8 * slot) : "memory");
            sts128(sb + OFF_P + slot * 2048 + warp * 512 + lane * 16, p0, p1, p2, p3);
            if (warp == 0 && quad == 0) {
                asm volatile("st.async.weak.shared::cluster.mbarrier::complete_tx::bytes.f32 [%0], %1, [%2];"
                             ::"r"(ra + slot * 64), "f"(a0), "r"(rfull + 8 * slot) : "memory");
                asm volatile("st.async.weak.shared::cluster.mbarrier::complete_tx::bytes.f32 [%0], %1, [%2];"
                             ::"r"(ra + slot * 64 + 32), "f"(a1), "r"(rfull + 8 * slot) : "memory");
                sts32f(sb + OFF_ALPHA + slot * 64 + g8 * 4, a0);
                sts32f(sb + OFF_ALPHA + slot * 64 + 32 + g8 * 4, a1);
            }
            __syncwarp();
            if (lane == 0) mbar_arrive(sb + BAR_PFULL + 8 * slot);
        }
        l0 += __shfl_xor_sync(0xffffffffu, l0, 1);
        l1 += __shfl_xor_sync(0xffffffffu, l1, 1);
        l0 += __shfl_xor_sync(0xffffffffu, l0, 2);
        l1 += __shfl_xor_sync(0xffffffffu, l1, 2);
        if (quad == 0) {
            sts32f(sb + OFF_LSUM + g8 * 16 + warp * 4, l0);
            sts32f(sb + OFF_LSUM + 128 + g8 * 16 + warp * 4, l1);
            if (warp == 0) { sts32f(sb + OFF_MROW + g8 * 4, mc0); sts32f(sb + OFF_MROW + 32 + g8 * 4, mc1); }
        }
        bar_sync(2, 128);
        if (warp == 0) {
            if (lane < 16) {
                const float4 lv = lds128f(sb + OFF_LSUM + lane * 16);
                const float l = (lv.x + lv.y) + (lv.z + lv.w), m = lds32f(sb + OFF_MROW + lane * 4);
                asm volatile("st.async.weak.shared::cluster.mbarrier::complete_tx::bytes.v2.f32 [%0], {%1,%2}, [%3];"
                             ::"r"(mapa(sb + OFF_STAT + lane * 8, rank ^ 1)), "f"(m), "f"(l), "r"(mapa(sb + BAR_STAT, rank ^ 1)) : "memory");
                mbar_wait(sb + BAR_STAT, 0);
                const float pm = lds32f(sb + OFF_STAT + lane * 8), pl = lds32f(sb + OFF_STAT + lane * 8 + 4);
                const float mm = fmaxf(m, pm);
                const float e = ex2(m - mm), pe = ex2(pm - mm);
                const float inv = __fdividef(1.f, rank ? pl * pe + l * e : l * e + pl * pe);
                sts32f(sb + OFF_F + lane * 4, e * inv);
                sts32f(sb + OFF_F + 64 + lane * 4, pe * inv);
            }
            __syncwarp();
            if (lane == 0) mbar_arrive(sb + BAR_F);
        }
        mbar_wait(sb + BAR_D, 0);
    } else {
        const int w = warp - 4;
        asm volatile("barrier.cluster.wait.acquire.aligned;" ::: "memory");
        const int src = w >> 1, ds = w & 1;
        uint4* const oout = pin(&g_scr.o[(((bh & 7) * 4 + src * 2 + (lane >> 4)) * 4 + rank * 2 + ds) * 128 + (bh >> 3) * 16 + (lane & 15)]);
        const uint32_t pbase = pin(sb + OFF_P + src * NP * 2048 + lane * 16), abase = pin(sb + OFF_ALPHA + src * NP * 64 + g8 * 4);
        const uint32_t pfull = pin(sb + BAR_PFULL + src * NP * 8);
        const uint32_t pempty = src ? mapa(sb + BAR_PEMPTY + 8 * NP, rank ^ 1) : mapa(sb + BAR_PEMPTY, rank);
        float o[4][4], t[2][4][4];
#pragma unroll
        for (int j = 0; j < 16; j++) (&o[0][0])[j] = (&t[0][0][0])[j] = (&t[1][0][0])[j] = 0.f;
        const uint32_t voff = ((rank ^ src) * 64 + (lane & 15)) * 128;
        const int vc = ds * 4 + (lane >> 4), vx = lane & 7;
        const uint32_t v0 = pin(sb + voff + ((vc ^ vx) << 4)), v1 = pin(sb + voff + (((vc + 2) ^ vx) << 4));
        pkt_store(oout, 0, 0, 0, 0, tag ^ 1);
        uint32_t p[4][4], b0[4][4], b1[4][4];
        float a0 = 0.f, a1 = 0.f;
        auto load_v = [&](int st) {
#pragma unroll
            for (int j = 0; j < 4; j++) {
                ldsm4t(b0[j], v0 + st * STAGE + j * 2048);
                ldsm4t(b1[j], v1 + st * STAGE + j * 2048);
            }
        };
        auto next_p = [&](int i) {
            const int slot = i % NP;
            mbar_wait(pfull + 8 * slot, (i / NP) & 1);
#pragma unroll
            for (int j = 0; j < 4; j++) lds128(p[j], pbase + slot * 2048 + j * 512);
            const float n0 = lds32f(abase + slot * 64), n1 = lds32f(abase + slot * 64 + 32);
            __syncwarp();
            if (lane == 0 && i < NT - NP) {
                if (w == 2) mbar_expect_tx(pfull + 8 * slot, 2048 + 64);
                asm volatile("mbarrier.arrive.relaxed.cluster.shared::cluster.b64 _, [%0];"
                             ::"r"(pempty + 8 * slot + ((p[3][3] | __float_as_uint(n1)) & zero)) : "memory");
            }
#pragma unroll
            for (int j = 0; j < 4; j++) {
                o[j][0] = fmaf(o[j][0], a0, t[0][j][0] + t[1][j][0]); o[j][1] = fmaf(o[j][1], a0, t[0][j][1] + t[1][j][1]);
                o[j][2] = fmaf(o[j][2], a1, t[0][j][2] + t[1][j][2]); o[j][3] = fmaf(o[j][3], a1, t[0][j][3] + t[1][j][3]);
            }
            a0 = n0; a1 = n1;
        };
        auto pv = [&]() {
#pragma unroll
            for (int j = 0; j < 16; j++) (&t[0][0][0])[j] = (&t[1][0][0])[j] = 0.f;
#pragma unroll
            for (int j = 0; j < 4; j++) {
                mma(t[j & 1][0], p[j], b0[j][0], b0[j][1]);
                mma(t[j & 1][1], p[j], b0[j][2], b0[j][3]);
                mma(t[j & 1][2], p[j], b1[j][0], b1[j][1]);
                mma(t[j & 1][3], p[j], b1[j][2], b1[j][3]);
            }
        };
        int st = KA + 1;
        uint32_t par = 0;
#pragma unroll 1
        for (int i = 0; i < NT - 1; i++) {
            mbar_wait(sb + BAR_FULL + 8 * st, par);
            load_v(st);
            next_p(i);
            pv();
            __syncwarp();
            if (lane == 0) mbar_arrive(sb + BAR_EMPTY + 8 * st);
            st += i < NT - KA - 1 ? 2 : 1;
            if (st >= NST) { st -= NST; par ^= 1; }
        }
        constexpr int LST = (2 * NT - 1) % NST, LPAR = ((2 * NT - 1) / NST) & 1;
        const bool landed = mbar_test(sb + BAR_FULL + 8 * LST, LPAR);
        if (landed) load_v(LST);
        next_p(NT - 1);
        mbar_wait(sb + BAR_F, 0);
        const float f0 = lds32f(sb + OFF_F + src * 64 + g8 * 4), f1 = lds32f(sb + OFF_F + src * 64 + 32 + g8 * 4);
        a0 *= f0; a1 *= f1;
#pragma unroll
        for (int j = 0; j < 4; j++) {
            o[j][0] *= a0; o[j][1] *= a0; o[j][2] *= a1; o[j][3] *= a1;
            asm volatile("" : "+f"(o[j][0]), "+f"(o[j][1]), "+f"(o[j][2]), "+f"(o[j][3]));
        }
        if (!landed) {
            mbar_wait(sb + BAR_FULL + 8 * LST, LPAR);
            load_v(LST);
        }
        pv();
#pragma unroll
        for (int j = 0; j < 4; j++) {
            o[j][0] = fmaf(t[0][j][0] + t[1][j][0], f0, o[j][0]); o[j][1] = fmaf(t[0][j][1] + t[1][j][1], f0, o[j][1]);
            o[j][2] = fmaf(t[0][j][2] + t[1][j][2], f1, o[j][2]); o[j][3] = fmaf(t[0][j][3] + t[1][j][3], f1, o[j][3]);
        }
        {
            const uint32_t mine = sb + OFF_MERGE + w * 1024 + lane * 16, theirs = sb + OFF_MERGE + (w ^ 2) * 1024 + lane * 16;
            float k[8];
#pragma unroll
            for (int j = 0; j < 4; j++) {
                k[2 * j] = src ? o[j][2] : o[j][0];
                k[2 * j + 1] = src ? o[j][3] : o[j][1];
            }
            sts128f(theirs, src ? o[0][0] : o[0][2], src ? o[0][1] : o[0][3], src ? o[1][0] : o[1][2], src ? o[1][1] : o[1][3]);
            sts128f(theirs + 512, src ? o[2][0] : o[2][2], src ? o[2][1] : o[2][3], src ? o[3][0] : o[3][2], src ? o[3][1] : o[3][3]);
            bar_sync(5 + ds, 64);
            const float4 r0 = lds128f(mine), r1 = lds128f(mine + 512);
            pkt_store(oout, pack_bf16(k[0] + r0.x, k[1] + r0.y), pack_bf16(k[2] + r0.z, k[3] + r0.w),
                      pack_bf16(k[4] + r1.x, k[5] + r1.y), pack_bf16(k[6] + r1.z, k[7] + r1.w), tag);
        }
        if (lane == 0) mbar_arrive(sb + BAR_D);
    }

    {
        uint32_t a[8][2][4];
        const int kr = (lane >> 4) * 8 + (lane & 7);
        const int wc = (lane >> 3) & 1, wx = (kr >> 1) & 3;
        const uint32_t wb0 = pin(sb + OFF_WO + (g * 128 + kr) * 64 + ((wc ^ wx) << 4));
        const uint32_t wb1 = pin(sb + OFF_WO + (g * 128 + kr) * 64 + (((wc + 2) ^ wx) << 4));
        const uint32_t red = pin(sb + OFF_PRED + rh * 8192 + lane * 16);
        const uint32_t rw = pin(red + g * 512), rr = pin(red + (g & 1) * 4096 + (g >> 1) * 2048);
        const uint32_t wobar = sb + BAR_WO + 8 * g;
        constexpr uint32_t wopar = 0;
        auto wo_within = [&](uint32_t clks) {
            uint32_t c0, c1;
            bool in;
            asm volatile("mov.u32 %0, %%clock;" : "=r"(c0));
            do {
                in = mbar_test(wobar, wopar);
                asm volatile("mov.u32 %0, %%clock;" : "=r"(c1));
            } while (!in && c1 - c0 < clks);
            return in;
        };
        Pkt v[8];
        const bool in0 = wo_within(O_DELAY);
        pkt_issue<8, 4, 128, 32>(v, oin);
        if (!in0) {
#pragma unroll 1
            for (int it = 0; !wo_within(O_PERIOD); it++) {
                uint32_t b[8];
#pragma unroll
                for (int i = 0; i < 8; i++) b[i] = v[i].bad(tag);
                if (it > (1 << 16)) __trap();
#pragma unroll
                for (int i = 0; i < 8; i++) pkt_reload(v[i], oin + (i >> 2) * 32 + (i & 3) * 128, b[i]);
            }
        }
#pragma unroll
        for (int ks = 0; ks < 8; ks++) {
            ldsm4t(a[ks][0], wb0 + ks * 1024);
            ldsm4t(a[ks][1], wb1 + ks * 1024);
        }
        pkt_poll<8, 4, 128, 32>(v, oin, tag | (a[7][1][3] & zero));
        float c[2][2][2][4];
#pragma unroll
        for (int j = 0; j < 32; j++) (&c[0][0][0][0])[j] = 0.f;
#pragma unroll
        for (int dq = 0; dq < 4; dq++)
#pragma unroll
            for (int t = 0; t < 2; t++) {
                mma(c[t][0][0], a[2 * dq][0], v[t * 4 + dq].w0(), v[t * 4 + dq].w1());
                mma(c[t][1][0], a[2 * dq][1], v[t * 4 + dq].w0(), v[t * 4 + dq].w1());
                mma(c[t][0][1], a[2 * dq + 1][0], v[t * 4 + dq].w2(), v[t * 4 + dq].w3());
                mma(c[t][1][1], a[2 * dq + 1][1], v[t * 4 + dq].w2(), v[t * 4 + dq].w3());
            }
#pragma unroll
        for (int t = 0; t < 2; t++)
#pragma unroll
            for (int mt = 0; mt < 2; mt++)
                sts128f(rw + t * 4096 + mt * 2048, c[t][mt][0][0] + c[t][mt][1][0], c[t][mt][0][1] + c[t][mt][1][1],
                        c[t][mt][0][2] + c[t][mt][1][2], c[t][mt][0][3] + c[t][mt][1][3]);
        bar_sync(3 + rh, 128);
        const float4 s0 = lds128f(rr), s1 = lds128f(rr + 512), s2 = lds128f(rr + 1024), s3 = lds128f(rr + 1536);
        pkt_store(pout, __float_as_uint((s0.x + s1.x) + (s2.x + s3.x)), __float_as_uint((s0.y + s1.y) + (s2.y + s3.y)),
                  __float_as_uint((s0.z + s1.z) + (s2.z + s3.z)), __float_as_uint((s0.w + s1.w) + (s2.w + s3.w)), tag);
    }

    {
        if (warp < 4) {
            Pkt v[2];
            spin(P_DELAY);
            pkt_load(v[0], pin_);
            pkt_load(v[1], pin_ + 128);
#pragma unroll 1
            for (int it = 0;; it++) {
                const uint32_t b0 = v[0].bad(tag), b1 = v[1].bad(tag);
                if (!any_bit0(or3(b0, b1, 0u))) break;
                pkt_reload(v[0], pin_, b0);
                pkt_reload(v[1], pin_ + 128, b1);
                if (it > (1 << 20)) __trap();
            }
            const float e0 = __uint_as_float(v[0].w0()) + __uint_as_float(v[1].w0()), e1 = __uint_as_float(v[0].w1()) + __uint_as_float(v[1].w1());
            const float e2 = __uint_as_float(v[0].w2()) + __uint_as_float(v[1].w2()), e3 = __uint_as_float(v[0].w3()) + __uint_as_float(v[1].w3());
            const bool hi = lane & 8, hi2 = lane & 16;
            const float k0 = (hi ? e1 : e0) + __shfl_xor_sync(0xffffffffu, hi ? e0 : e1, 8);
            const float k1 = (hi ? e3 : e2) + __shfl_xor_sync(0xffffffffu, hi ? e2 : e3, 8);
            const uint32_t res = pack_bf16((hi2 ? k1 : k0) + __shfl_xor_sync(0xffffffffu, hi2 ? k0 : k1, 16), 0.f);
            asm volatile("st.global.u16 [%0], %1;" ::"l"(optr), "h"((uint16_t)res) : "memory");
        }
        if ((cta | warp | lane) == 0)
            asm volatile("st.relaxed.gpu.global.u32 [%0], %1;" ::"l"(&g_scr.epoch), "r"(epoch + 1) : "memory");
    }
}

__global__ void fb_proj(const __nv_bfloat16* a_bf, const float* a_f, const __nv_bfloat16* w, int K, int N, float* o_f,
                        __nv_bfloat16* o_bf) {
    const int c = blockIdx.x * blockDim.x + threadIdx.x, r = blockIdx.y;
    float s = 0.f;
    for (int k = 0; k < K; k++) s += (a_bf ? __bfloat162float(a_bf[r * K + k]) : a_f[r * K + k]) * __bfloat162float(w[k * N + c]);
    if (o_bf) o_bf[r * N + c] = __float2bfloat16(s);
    else o_f[r * N + c] = __bfloat162float(__float2bfloat16(s));
}
__global__ void fb_attn(const __nv_bfloat16* kc, const __nv_bfloat16* vc) {
    __shared__ float sc[2048], red[128];
    const int r = blockIdx.x, hq = blockIdx.y, t = threadIdx.x;
    const size_t base = (size_t)((r >> 2) * 8 + (hq >> 2)) * 2048 * 128;
    float m = -INFINITY, l = 0.f, acc = 0.f;
    for (int j = t; j < 2048; j += 128) {
        float s = 0.f;
        for (int d = 0; d < 128; d++) s += g_scr.fq[r * 4096 + hq * 128 + d] * __bfloat162float(kc[base + j * 128 + d]);
        sc[j] = s * 0.08838834764831845f;
        m = fmaxf(m, sc[j]);
    }
    red[t] = m;
    __syncthreads();
    for (int i = 0; i < 128; i++) m = fmaxf(m, red[i]);
    for (int j = t; j < 2048; j += 128) sc[j] = __expf(sc[j] - m);
    __syncthreads();
    for (int j = 0; j < 2048; j++) {
        l += sc[j];
        acc += sc[j] * __bfloat162float(vc[base + j * 128 + t]);
    }
    g_scr.fo[r * 4096 + hq * 128 + t] = __bfloat162float(__float2bfloat16(acc / l));
}

typedef CUresult (*EncodeFn)(CUtensorMap*, CUtensorMapDataType, cuuint32_t, void*, const cuuint64_t*, const cuuint64_t*,
                             const cuuint32_t*, const cuuint32_t*, CUtensorMapInterleave, CUtensorMapSwizzle,
                             CUtensorMapL2promotion, CUtensorMapFloatOOBfill);

static void encode(EncodeFn fn, CUtensorMap* m, void* p, int rank, const cuuint64_t* dims, const cuuint64_t* strides,
                   const cuuint32_t* box, CUtensorMapSwizzle sw) {
    const cuuint32_t es[3] = {1, 1, 1};
    fn(m, CU_TENSOR_MAP_DATA_TYPE_BFLOAT16, rank, p, dims, strides, box, es, CU_TENSOR_MAP_INTERLEAVE_NONE, sw,
       CU_TENSOR_MAP_L2_PROMOTION_L2_256B, CU_TENSOR_MAP_FLOAT_OOB_FILL_NONE);
}

}

extern "C" void kernel_launch(void* const* d_in, const int* in_sizes, int n_in, void* d_out, int out_size) {
    using namespace gqa;
    static EncodeFn fn = nullptr;
    static uint32_t slot_ns = SLOT_NS;
    static bool fits = false;
    if (!fn) {
        int dev = 0, khz = 0, bits = 0;
        cudaGetDevice(&dev);
        cudaDeviceGetAttribute(&khz, cudaDevAttrMemoryClockRate, dev);
        cudaDeviceGetAttribute(&bits, cudaDevAttrGlobalMemoryBusWidth, dev);
        if (khz > 0 && bits > 0) slot_ns = (uint32_t)((double)NCTA * STAGE / (0.955 * 2.0 * khz * 1e-6 * (bits / 8)));
        void* p = nullptr;
        cudaDriverEntryPointQueryResult qr;
        cudaGetDriverEntryPoint("cuTensorMapEncodeTiled", &p, cudaEnableDefault, &qr);
        fn = (EncodeFn)p;
        cudaFuncSetAttribute(gqa_kernel, cudaFuncAttributeMaxDynamicSharedMemorySize, SMEM_BYTES);
        cudaLaunchConfig_t cfg = {};
        cfg.gridDim = dim3(NCTA);
        cfg.blockDim = dim3(288);
        cfg.dynamicSmemBytes = SMEM_BYTES;
        int clusters = 0;
        fits = cudaOccupancyMaxActiveClusters(&clusters, gqa_kernel, &cfg) == cudaSuccess && clusters >= NCTA / 2;
    }
    if (!fits) {
        Scratch* scr = nullptr;
        cudaGetSymbolAddress((void**)&scr, g_scr);
        float *fq = scr->fq, *fo = scr->fo;
        fb_proj<<<dim3(16, 32), 256, 0, cudaStreamPerThread>>>((const __nv_bfloat16*)d_in[0], nullptr, (const __nv_bfloat16*)d_in[3], 512,
                                                               4096, fq, nullptr);
        fb_attn<<<dim3(32, 32), 128, 0, cudaStreamPerThread>>>((const __nv_bfloat16*)d_in[1], (const __nv_bfloat16*)d_in[2]);
        fb_proj<<<dim3(2, 32), 256, 0, cudaStreamPerThread>>>(nullptr, fo, (const __nv_bfloat16*)d_in[4], 4096, 512, nullptr,
                                                              (__nv_bfloat16*)d_out);
        return;
    }
    CUtensorMap tmK, tmV, tmX, tmWq, tmWo;
    {
        const cuuint64_t dims[3] = {64, 8 * 8 * 2048, 2}, str[2] = {256, 128};
        const cuuint32_t box[3] = {64, 64, 2};
        encode(fn, &tmK, d_in[1], 3, dims, str, box, CU_TENSOR_MAP_SWIZZLE_128B);
        const cuuint64_t dv[2] = {128, 8 * 8 * 2048}, sv[1] = {256};
        const cuuint32_t bv[2] = {64, 128};
        encode(fn, &tmV, d_in[2], 2, dv, sv, bv, CU_TENSOR_MAP_SWIZZLE_128B);
    }
    {
        const cuuint64_t dims[3] = {64, 32, 8}, str[2] = {1024, 128};
        const cuuint32_t box[3] = {64, 32, 8};
        encode(fn, &tmX, d_in[0], 3, dims, str, box, CU_TENSOR_MAP_SWIZZLE_128B);
    }
    {
        const cuuint64_t dq[2] = {4096, 512}, sq[1] = {8192}, dw[2] = {512, 4096}, sw[1] = {1024};
        const cuuint32_t box[2] = {32, 256};
        encode(fn, &tmWq, d_in[3], 2, dq, sq, box, CU_TENSOR_MAP_SWIZZLE_64B);
        const cuuint32_t boxo[2] = {32, 128};
        encode(fn, &tmWo, d_in[4], 2, dw, sw, boxo, CU_TENSOR_MAP_SWIZZLE_64B);
    }
    gqa_kernel<<<NCTA, 288, SMEM_BYTES, cudaStreamPerThread>>>(Ptrs{{(const uint8_t*)d_in[3], nullptr}}, (__nv_bfloat16*)d_out, slot_ns, 0u, tmK, tmV, tmX,
                                                               tmWq, tmWo);
}
```

```cpp
#include <cuda_runtime.h>
#include <cuda_bf16.h>
#include <cuda.h>
#include <stdint.h>

namespace gqa {

constexpr int PA_NS = 2780;
constexpr int SLOT_NS = 655;
constexpr int WO_SLOT = 2895;
constexpr int WO_STEP = 65;
constexpr int Q_DELAY_NS = 1000;
constexpr int O_DELAY = 900;
constexpr int O_PERIOD = 350;
constexpr int P_DELAY = 330;
constexpr int PF_BYTES = 8192;

constexpr int NCTA = 128;
constexpr int NT = 16;
constexpr int NST = 13;
constexpr int NST0 = 10;
constexpr int WIN0 = 3;
constexpr int WIN = 8;
constexpr int WSW = 8;
constexpr int KA = 2;
constexpr int NP = 4;
constexpr int STAGE = 16384;

constexpr int OFF_WQ = NST0 * STAGE;
constexpr int OFF_X = OFF_WQ + 32768;
constexpr int OFF_QRED = OFF_X;
constexpr int OFF_WO = ((2 * NT) % NST) * STAGE;
constexpr int OFF_P = NST * STAGE;
constexpr int OFF_MERGE = (((2 * NT) % NST) + 3) * STAGE;
constexpr int OFF_ALPHA = (NST + 1) * STAGE + 512;
constexpr int OFF_WMAX = OFF_ALPHA + 2 * NP * 64;
constexpr int OFF_LSUM = OFF_WMAX + 512;
constexpr int OFF_MROW = OFF_LSUM + 256;
constexpr int OFF_STAT = OFF_MROW + 64;
constexpr int OFF_F = OFF_STAT + 128;
constexpr int OFF_PRED = (((2 * NT) % NST) + 2) * STAGE;
constexpr int OFF_BAR = (NST + 1) * STAGE;
constexpr int BAR_FULL = OFF_BAR;
constexpr int BAR_EMPTY = BAR_FULL + 8 * NST;
constexpr int BAR_PFULL = BAR_EMPTY + 8 * NST;
constexpr int BAR_PEMPTY = BAR_PFULL + 16 * NP;
constexpr int BAR_W = BAR_PEMPTY + 16 * NP;
constexpr int BAR_STAT = BAR_W + 8;
constexpr int BAR_F = BAR_STAT + 8;
constexpr int BAR_D = BAR_F + 8;
constexpr int BAR_WO = BAR_D + 8;
constexpr int SMEM_BYTES = OFF_F + 128;
static_assert(2 * NP * 2048 <= STAGE, "P slots overflow");
static_assert(BAR_WO + 32 <= OFF_ALPHA, "barriers overflow");
static_assert((2 * NT) % NST + 3 < NST, "wo / partial slots must not wrap");
static_assert(SMEM_BYTES <= 232448, "too much shared memory");

struct __align__(1024) Scratch {
    uint4 q[32 * 4 * 8 * 16];
    uint4 o[32 * 4 * 8 * 16];
    uint4 p[128 * 8 * 32];
    unsigned epoch;
    float fq[32 * 4096], fo[32 * 4096];
};
__device__ Scratch g_scr;

__device__ __forceinline__ void mbar_init(uint32_t bar, uint32_t cnt) {
    asm volatile("mbarrier.init.shared::cta.b64 [%0], %1;" ::"r"(bar), "r"(cnt) : "memory");
}
__device__ __forceinline__ void mbar_expect_tx(uint32_t bar, uint32_t bytes) {
    asm volatile("mbarrier.arrive.expect_tx.shared::cta.b64 _, [%0], %1;" ::"r"(bar), "r"(bytes) : "memory");
}
__device__ __forceinline__ void mbar_arrive(uint32_t bar) {
    asm volatile("mbarrier.arrive.shared::cta.b64 _, [%0];" ::"r"(bar) : "memory");
}
__device__ __forceinline__ bool mbar_try(uint32_t bar, uint32_t parity) {
    uint32_t ok;
    asm volatile("{\n.reg .pred p;\nmbarrier.try_wait.parity.shared::cta.b64 p, [%1], %2;\nselp.u32 %0, 1, 0, p;\n}"
                 : "=r"(ok) : "r"(bar), "r"(parity) : "memory");
    return ok;
}
__device__ __forceinline__ bool mbar_test(uint32_t bar, uint32_t parity) {
    uint32_t ok;
    asm volatile("{\n.reg .pred p;\nmbarrier.test_wait.parity.shared::cta.b64 p, [%1], %2;\nselp.u32 %0, 1, 0, p;\n}"
                 : "=r"(ok) : "r"(bar), "r"(parity) : "memory");
    return ok;
}
__device__ __forceinline__ void mbar_wait(uint32_t bar, uint32_t parity) {
#pragma unroll 1
    for (int i = 0; !mbar_try(bar, parity); i++)
        if (i > (1 << 20)) __trap();
}
__device__ __forceinline__ void tma2d(uint32_t dst, const CUtensorMap* m, int c0, int c1, uint32_t bar) {
    asm volatile("cp.async.bulk.tensor.2d.shared::cluster.global.mbarrier::complete_tx::bytes [%0], [%1, {%3, %4}], [%2];"
                 ::"r"(dst), "l"(m), "r"(bar), "r"(c0), "r"(c1) : "memory");
}
__device__ __forceinline__ void tma3d(uint32_t dst, const CUtensorMap* m, int c0, int c1, int c2, uint32_t bar) {
    asm volatile("cp.async.bulk.tensor.3d.shared::cluster.global.mbarrier::complete_tx::bytes [%0], [%1, {%3, %4, %5}], [%2];"
                 ::"r"(dst), "l"(m), "r"(bar), "r"(c0), "r"(c1), "r"(c2) : "memory");
}
__device__ __forceinline__ void tma2d_hint(uint32_t dst, const CUtensorMap* m, int c0, int c1, uint32_t bar, uint64_t pol) {
    asm volatile("cp.async.bulk.tensor.2d.shared::cluster.global.mbarrier::complete_tx::bytes.L2::cache_hint [%0], [%1, {%3, %4}], [%2], %5;"
                 ::"r"(dst), "l"(m), "r"(bar), "r"(c0), "r"(c1), "l"(pol) : "memory");
}
__device__ __forceinline__ uint32_t mapa(uint32_t addr, uint32_t cta_rank) {
    uint32_t r;
    asm("mapa.shared::cluster.u32 %0, %1, %2;" : "=r"(r) : "r"(addr), "r"(cta_rank));
    return r;
}
__device__ __forceinline__ void tma3d_hint(uint32_t dst, const CUtensorMap* m, int c0, int c1, int c2, uint32_t bar, uint64_t pol) {
    asm volatile("cp.async.bulk.tensor.3d.shared::cluster.global.mbarrier::complete_tx::bytes.L2::cache_hint [%0], [%1, {%3, %4, %5}], [%2], %6;"
                 ::"r"(dst), "l"(m), "r"(bar), "r"(c0), "r"(c1), "r"(c2), "l"(pol) : "memory");
}
__device__ __forceinline__ void ldsm4(uint32_t (&r)[4], uint32_t addr) {
    asm volatile("ldmatrix.sync.aligned.m8n8.x4.shared.b16 {%0,%1,%2,%3}, [%4];"
                 : "=r"(r[0]), "=r"(r[1]), "=r"(r[2]), "=r"(r[3]) : "r"(addr) : "memory");
}
__device__ __forceinline__ void ldsm4t(uint32_t (&r)[4], uint32_t addr) {
    asm volatile("ldmatrix.sync.aligned.m8n8.x4.trans.shared.b16 {%0,%1,%2,%3}, [%4];"
                 : "=r"(r[0]), "=r"(r[1]), "=r"(r[2]), "=r"(r[3]) : "r"(addr) : "memory");
}
__device__ __forceinline__ void mma(float (&c)[4], const uint32_t (&a)[4], uint32_t b0, uint32_t b1) {
    asm volatile("mma.sync.aligned.m16n8k16.row.col.f32.bf16.bf16.f32 {%0,%1,%2,%3}, {%4,%5,%6,%7}, {%8,%9}, {%0,%1,%2,%3};"
                 : "+f"(c[0]), "+f"(c[1]), "+f"(c[2]), "+f"(c[3])
                 : "r"(a[0]), "r"(a[1]), "r"(a[2]), "r"(a[3]), "r"(b0), "r"(b1));
}
__device__ __forceinline__ uint32_t pack_bf16(float lo, float hi) {
    uint32_t r;
    asm("cvt.rn.bf16x2.f32 %0, %1, %2;" : "=r"(r) : "f"(hi), "f"(lo));
    return r;
}
__device__ __forceinline__ float ex2(float x) {
    float y;
    asm("ex2.approx.ftz.f32 %0, %1;" : "=f"(y) : "f"(x));
    return y;
}
__device__ __forceinline__ void sts128(uint32_t addr, uint32_t a, uint32_t b, uint32_t c, uint32_t d) {
    asm volatile("st.shared.v4.b32 [%0], {%1,%2,%3,%4};" ::"r"(addr), "r"(a), "r"(b), "r"(c), "r"(d) : "memory");
}
__device__ __forceinline__ void sts128f(uint32_t addr, float a, float b, float c, float d) {
    asm volatile("st.shared.v4.f32 [%0], {%1,%2,%3,%4};" ::"r"(addr), "f"(a), "f"(b), "f"(c), "f"(d) : "memory");
}
__device__ __forceinline__ void sts32f(uint32_t addr, float a) {
    asm volatile("st.shared.f32 [%0], %1;" ::"r"(addr), "f"(a) : "memory");
}
__device__ __forceinline__ void lds128(uint32_t (&r)[4], uint32_t addr) {
    asm volatile("ld.shared.v4.b32 {%0,%1,%2,%3}, [%4];" : "=r"(r[0]), "=r"(r[1]), "=r"(r[2]), "=r"(r[3]) : "r"(addr) : "memory");
}
__device__ __forceinline__ float4 lds128f(uint32_t addr) {
    float4 v;
    asm volatile("ld.shared.v4.f32 {%0,%1,%2,%3}, [%4];" : "=f"(v.x), "=f"(v.y), "=f"(v.z), "=f"(v.w) : "r"(addr) : "memory");
    return v;
}
__device__ __forceinline__ float lds32f(uint32_t addr) {
    float v;
    asm volatile("ld.shared.f32 %0, [%1];" : "=f"(v) : "r"(addr) : "memory");
    return v;
}
__device__ __forceinline__ void bar_sync(int id, int n) { asm volatile("bar.sync %0, %1;" ::"r"(id), "r"(n) : "memory"); }
template <typename T> __device__ __forceinline__ T* pin(T* p) { asm volatile("" : "+l"(p)); return p; }
__device__ __forceinline__ uint32_t pin(uint32_t v) { asm volatile("" : "+r"(v)); return v; }

struct Pkt {
    uint64_t lo, hi;
    __device__ __forceinline__ uint32_t w0() const { return (uint32_t)lo; }
    __device__ __forceinline__ uint32_t w1() const { return (uint32_t)(lo >> 32); }
    __device__ __forceinline__ uint32_t w2() const { return (uint32_t)hi; }
    __device__ __forceinline__ uint32_t w3() const { return (uint32_t)(hi >> 32); }
    __device__ __forceinline__ uint32_t bad(uint32_t tag) const {
        uint32_t r;
        asm("lop3.b32 %0, %1, %2, %3, 0x7E;" : "=r"(r) : "r"(w0()), "r"(w2()), "r"(tag));
        return r;
    }
};
__device__ __forceinline__ void pkt_store(uint4* p, uint32_t a, uint32_t b, uint32_t c, uint32_t d, uint32_t tag) {
    a = (a & ~1u) | tag;
    c = (c & ~1u) | tag;
    asm volatile("{\n.reg .b64 lo, hi;\nmov.b64 lo, {%1,%2};\nmov.b64 hi, {%3,%4};\n"
                 "st.relaxed.gpu.global.v2.b64 [%0], {lo, hi};\n}" ::"l"(p), "r"(a), "r"(b), "r"(c), "r"(d) : "memory");
}
__device__ __forceinline__ uint32_t pack_bf16_tagged(float lo, float hi, uint32_t tag) {
    uint32_t r = pack_bf16(lo, hi);
    if ((r ^ tag) & 1u) {
        const uint32_t mag = r & 0x7fffu;
        const bool up = mag == 0 || (fabsf(lo) > __uint_as_float(mag << 16) && mag < 0x7f7fu);
        r += up ? 1u : 0xffffffffu;
    }
    return r;
}
__device__ __forceinline__ void pkt_load(Pkt& v, const uint4* p) {
    asm volatile("ld.relaxed.gpu.global.v2.b64 {%0, %1}, [%2];" : "=l"(v.lo), "=l"(v.hi) : "l"(p) : "memory");
}
__device__ __forceinline__ void pkt_reload(Pkt& v, const uint4* p, uint32_t bad) {
    asm volatile("{\n.reg .pred p;\n.reg .b32 t;\nand.b32 t, %3, 1;\nsetp.ne.u32 p, t, 0;\n"
                 "@p ld.relaxed.gpu.global.v2.b64 {%0, %1}, [%2];\n}"
                 : "+l"(v.lo), "+l"(v.hi) : "l"(p), "r"(bad) : "memory");
}
__device__ __forceinline__ uint32_t or3(uint32_t a, uint32_t b, uint32_t c) {
    uint32_t r;
    asm("lop3.b32 %0, %1, %2, %3, 0xFE;" : "=r"(r) : "r"(a), "r"(b), "r"(c));
    return r;
}
__device__ __forceinline__ bool any_bit0(uint32_t x) {
    uint32_t r;
    asm volatile("{\n.reg .pred p, q;\n.reg .b32 t;\nand.b32 t, %1, 1;\nsetp.ne.u32 p, t, 0;\nvote.sync.any.pred q, p, 0xffffffff;\n"
                 "selp.u32 %0, 1, 0, q;\n}" : "=r"(r) : "r"(x));
    return r;
}
template <int N, int N0, int S0, int S1>
__device__ __forceinline__ void pkt_issue(Pkt (&v)[N], const uint4* p) {
#pragma unroll
    for (int i = 0; i < N; i++) pkt_load(v[i], p + (i / N0) * S1 + (i % N0) * S0);
}
template <int N, int N0, int S0, int S1>
__device__ __forceinline__ void pkt_poll(Pkt (&v)[N], const uint4* p, uint32_t tag) {
    static_assert(N == 1 || N == 8, "");
#pragma unroll 1
    for (int it = 0;; it++) {
        uint32_t b[N];
#pragma unroll
        for (int i = 0; i < N; i++) b[i] = v[i].bad(tag);
        uint32_t bad = b[0];
        if (N == 8) bad = or3(or3(b[0], b[1 % N], b[2 % N]), or3(b[3 % N], b[4 % N], b[5 % N]), or3(b[6 % N], b[7 % N], 0u));
        if (!any_bit0(bad)) break;
#pragma unroll
        for (int i = 0; i < N; i++) pkt_reload(v[i], p + (i / N0) * S1 + (i % N0) * S0, b[i]);
        if (it > (1 << 20)) __trap();
    }
}

__device__ __forceinline__ uint32_t now_ns() {
    uint32_t t;
    asm volatile("mov.u32 %0, %%globaltimer_lo;" : "=r"(t));
    return t;
}
__device__ __forceinline__ void spin(uint32_t clks) {
    uint32_t c0, c1;
    asm volatile("mov.u32 %0, %%clock;" : "=r"(c0));
    do { asm volatile("mov.u32 %0, %%clock;" : "=r"(c1)); } while (c1 - c0 < clks);
}
__device__ __forceinline__ void wait_until(uint32_t t) {
#pragma unroll 1
    for (int i = 0; (int)(now_ns() - t) < 0 && i < (1 << 16); i++) {}
}

struct Ptrs { const uint8_t* p[2]; };

__global__ void __cluster_dims__(2, 1, 1) __launch_bounds__(288, 1)
gqa_kernel(const __grid_constant__ Ptrs ptrs, __nv_bfloat16* __restrict__ out, uint32_t slot_ns, uint32_t zero,
           const __grid_constant__ CUtensorMap tmK, const __grid_constant__ CUtensorMap tmV,
           const __grid_constant__ CUtensorMap tmX, const __grid_constant__ CUtensorMap tmWq,
           const __grid_constant__ CUtensorMap tmWo) {
    const uint32_t tstart = now_ns();
    if (threadIdx.x == 32)
        asm volatile("cp.async.bulk.prefetch.L2.global [%0], %1;" ::"l"(ptrs.p[blockIdx.x >> 10] + blockIdx.x * PF_BYTES), "r"(PF_BYTES)
                     : "memory");
    extern __shared__ __align__(1024) uint8_t smem_raw[];
    const uint32_t sb = pin((uint32_t)__cvta_generic_to_shared(smem_raw));
    if (threadIdx.x == 0) {
        mbar_init(sb + BAR_W, 1);
        asm volatile("fence.mbarrier_init.release.cluster;" ::: "memory");
        mbar_expect_tx(sb + BAR_W, 65536);
        tma2d(sb + OFF_WQ, &tmWq, blockIdx.x * 32, 0, sb + BAR_W);
        tma2d(sb + OFF_WQ + 16384, &tmWq, blockIdx.x * 32, 256, sb + BAR_W);
        tma3d(sb + OFF_X, &tmX, 0, 0, 0, sb + BAR_W);
    }
    const int warp = __shfl_sync(0xffffffffu, threadIdx.x >> 5, 0), lane = pin(threadIdx.x & 31);
    const int cta = pin(blockIdx.x), rank = cta & 1, bh = cta >> 1;

    if (warp == 8) {
        const int row0 = bh * 2048 + rank * 64;
        uint64_t pol;
        asm volatile("createpolicy.fractional.L2::evict_first.b64 %0, 1.0;" : "=l"(pol));
        auto issue = [&](int n) {
            const bool isv = n >= 2 * NT - KA || (n >= KA && ((n - KA) & 1));
            const int t = n < KA ? n : n >= 2 * NT - KA ? n - NT : isv ? (n - KA) >> 1 : (n + KA) >> 1;
            const int st = n % NST;
            if (isv) tma2d_hint(sb + st * STAGE, &tmV, rank * 64, bh * 2048 + t * 128, sb + BAR_FULL + 8 * st, pol);
            else tma3d_hint(sb + st * STAGE, &tmK, 0, row0 + t * 128, 0, sb + BAR_FULL + 8 * st, pol);
        };
        if (lane == 0) {
            if (sb & 1023) __trap();
#pragma unroll
            for (int i = 0; i < WIN0; i++) mbar_init(sb + BAR_FULL + 8 * i, 1);
            asm volatile("fence.mbarrier_init.release.cluster;" ::: "memory");
#pragma unroll
            for (int n = 0; n < WIN0; n++) {
                mbar_expect_tx(sb + BAR_FULL + 8 * n, STAGE);
                issue(n);
            }
            for (int i = WIN0; i < NST; i++) mbar_init(sb + BAR_FULL + 8 * i, 1);
            for (int i = 0; i < NST; i++) mbar_init(sb + BAR_EMPTY + 8 * i, 4);
            for (int i = 0; i < NP; i++) {
                mbar_init(sb + BAR_PFULL + 8 * i, 4);
                mbar_init(sb + BAR_PFULL + 8 * (NP + i), 1);
                mbar_expect_tx(sb + BAR_PFULL + 8 * (NP + i), 2048 + 64);
                mbar_init(sb + BAR_PEMPTY + 8 * i, 2);
                mbar_init(sb + BAR_PEMPTY + 8 * (NP + i), 2);
            }
            mbar_init(sb + BAR_STAT, 1);
            mbar_init(sb + BAR_F, 1);
            mbar_init(sb + BAR_D, 4);
            mbar_expect_tx(sb + BAR_STAT, 128);
            for (int i = 0; i < 4; i++) {
                mbar_init(sb + BAR_WO + 8 * i, 1);
                mbar_expect_tx(sb + BAR_WO + 8 * i, 8192);
            }
            asm volatile("fence.mbarrier_init.release.cluster;" ::: "memory");
            asm volatile("prefetch.tensormap [%0];" ::"l"(&tmWo) : "memory");
        }
        __syncthreads();
        asm volatile("barrier.cluster.arrive.relaxed.aligned;" ::: "memory");
        if (lane == 0) {
            auto wait_free = [&](int n) {
                const int st = n % NST, k = n / NST;
                if (st >= NST0) mbar_wait(sb + BAR_EMPTY + 8 * st, k & 1);
                else if (k) mbar_wait(sb + BAR_EMPTY + 8 * st, (k - 1) & 1);
            };
            const uint32_t t3 = tstart + PA_NS;
#pragma unroll
            for (int n = WIN0; n < 2 * NT; n++) {
                wait_free(n);
                mbar_expect_tx(sb + BAR_FULL + 8 * (n % NST), STAGE);
                if (n < WSW || n >= WSW + WIN - WIN0) {
                    const int d = n - (n < WSW ? WIN0 : WIN);
                    mbar_wait(sb + BAR_FULL + 8 * (d % NST), (d / NST) & 1);
                }
                if (n >= WSW) wait_until(t3 + (n - 3) * slot_ns);
                issue(n);
            }
            wait_free(2 * NT); wait_free(2 * NT + 1); wait_free(2 * NT + 2);
#pragma unroll
            for (int g = 0; g < 4; g++) {
                wait_until(t3 + (WO_SLOT + g * WO_STEP) * slot_ns / 100);
                tma2d(sb + OFF_WO + g * 8192, &tmWo, (cta & 15) * 32, (cta >> 4) * 512 + g * 128, sb + BAR_WO + 8 * g);
            }
        }
        return;
    }

    unsigned epoch;
    asm volatile("ld.relaxed.gpu.global.u32 %0, [%1];" : "=r"(epoch) : "l"(&g_scr.epoch) : "memory");
    const int g8 = lane >> 2, quad = lane & 3;
    const int rh = warp >> 2, g = (warp + 2 * rh) & 3;
    const uint4* const oin = pin(&g_scr.o[((cta >> 4) * 4 + g) * 512 + rh * 64 + lane]);
    uint4* const pout = pin(&g_scr.p[(((rh * 2 + (g & 1)) * 32 + (cta & 15) * 2 + (g >> 1)) * 8 + (cta >> 4)) * 32 + quad * 8 + g8]);
    const uint4* const pin_ = pin(&g_scr.p[(cta * 8 + (lane >> 3)) * 32 + (warp & 3) * 8 + (lane & 7)]);
    __nv_bfloat16* const optr = pin(out + ((cta >> 5) * 8 + (warp & 3) * 2 + ((lane >> 3) & 1)) * 512 + (cta & 31) * 16 + (lane & 7) +
                                    (lane >> 4) * 8);
    __syncthreads();

    {
        const int kq = warp & 3, mt = warp >> 2;
        float c[4][4];
#pragma unroll
        for (int j = 0; j < 4; j++) c[j][0] = c[j][1] = c[j][2] = c[j][3] = 0.f;
        const int ar = mt * 16 + (lane & 15);
        const uint32_t abase = sb + OFF_X + kq * 8192 + ar * 128;
        const int br = lane & 15;
        const uint32_t bbase = sb + OFF_WQ + (kq * 128 + br) * 64;
        if (warp < 4) pkt_store(&g_scr.q[cta * 128 + warp * 32 + lane], 0, 0, 0, 0, epoch & 1);
        pkt_store(pout, 0, 0, 0, 0, epoch & 1);
        mbar_wait(sb + BAR_W, 0);
#pragma unroll
        for (int ks = 0; ks < 8; ks++) {
            uint32_t a[4], b0[4], b1[4];
            ldsm4(a, abase + (ks >> 2) * 4096 + ((((ks & 3) * 2 + (lane >> 4)) ^ (ar & 7)) << 4));
            ldsm4t(b0, bbase + ks * 1024 + (((lane >> 4) ^ ((br >> 1) & 3)) << 4));
            ldsm4t(b1, bbase + ks * 1024 + (((2 + (lane >> 4)) ^ ((br >> 1) & 3)) << 4));
            mma(c[0], a, b0[0], b0[1]);
            mma(c[1], a, b0[2], b0[3]);
            mma(c[2], a, b1[0], b1[1]);
            mma(c[3], a, b1[2], b1[3]);
        }
        bar_sync(1, 256);
        asm volatile("barrier.cluster.arrive.relaxed.aligned;" ::: "memory");
        const uint32_t rb = sb + OFF_QRED + (kq * 2 + mt) * 2048 + lane * 16;
        sts128f(rb, c[0][0], c[0][1], c[1][0], c[1][1]);
        sts128f(rb + 512, c[2][0], c[2][1], c[3][0], c[3][1]);
        sts128f(rb + 1024, c[0][2], c[0][3], c[1][2], c[1][3]);
        sts128f(rb + 1536, c[2][2], c[2][3], c[3][2], c[3][3]);
        bar_sync(1, 256);
    }
    const uint32_t tag = pin((epoch + 1) & 1);

    if (warp < 4) {
        {
            const uint32_t rb = sb + OFF_QRED + warp * 1024 + lane * 16;
            float4 s0 = lds128f(rb), s1 = lds128f(rb + 512);
#pragma unroll
            for (int kq = 1; kq < 4; kq++) {
                float4 t0 = lds128f(rb + kq * 4096), t1 = lds128f(rb + kq * 4096 + 512);
                s0.x += t0.x; s0.y += t0.y; s0.z += t0.z; s0.w += t0.w;
                s1.x += t1.x; s1.y += t1.y; s1.z += t1.z; s1.w += t1.w;
            }
            pkt_store(&g_scr.q[cta * 128 + warp * 32 + lane], pack_bf16_tagged(s0.x, s0.y, tag), pack_bf16(s0.z, s0.w),
                      pack_bf16_tagged(s1.x, s1.y, tag), pack_bf16(s1.z, s1.w), tag);
            __syncwarp();
            if (lane < NST - NST0) mbar_arrive(sb + BAR_EMPTY + 8 * (NST0 + lane));
        }
        __nanosleep(Q_DELAY_NS);
        uint32_t q[8][4];
        {
            Pkt v[8];
            const uint4* qp = &g_scr.q[(((bh & 7) * 4 + (lane >> 4)) * 4) * 128 + (bh >> 3) * 16 + (lane & 15)];
            pkt_issue<8, 4, 128, 1024>(v, qp);
            pkt_poll<8, 4, 128, 1024>(v, qp, tag);
#pragma unroll
            for (int dq = 0; dq < 4; dq++) {
                const Pkt &a = v[dq], &b = v[4 + dq];
                q[2 * dq][0] = a.w0();     q[2 * dq][1] = b.w0();     q[2 * dq][2] = a.w1();     q[2 * dq][3] = b.w1();
                q[2 * dq + 1][0] = a.w2(); q[2 * dq + 1][1] = b.w2(); q[2 * dq + 1][2] = a.w3(); q[2 * dq + 1][3] = b.w3();
            }
        }
        asm volatile("barrier.cluster.wait.acquire.aligned;" ::: "memory");
        constexpr float C = 0.08838834764831845f * 1.4426950408889634f;
        float mc0 = -INFINITY, mc1 = -INFINITY, l0 = 0.f, l1 = 0.f;
        const int key = warp * 16 + (lane >> 4) * 8 + (lane & 7);
        const uint32_t koff = key * 128;
        const int ksel = (lane >> 3) & 1, kx = lane & 7;
        const uint32_t rp = mapa(sb + OFF_P + NP * 2048 + warp * 512 + lane * 16, rank ^ 1);
        const uint32_t ra = mapa(sb + OFF_ALPHA + NP * 64 + g8 * 4, rank ^ 1), rfull = mapa(sb + BAR_PFULL + 8 * NP, rank ^ 1);
        int st = 0;
        uint32_t par = 0;
#pragma unroll 1
        for (int i = 0; i < NT; i++) {
            const uint32_t kb = sb + st * STAGE + koff;
            float s[2][2][4];
#pragma unroll
            for (int j = 0; j < 4; j++) s[0][0][j] = s[0][1][j] = s[1][0][j] = s[1][1][j] = 0.f;
            mbar_wait(sb + BAR_FULL + 8 * st, par);
#pragma unroll
            for (int ks = 0; ks < 8; ks++) {
                uint32_t b[4];
                ldsm4(b, kb + (ks >> 2) * 8192 + ((((ks & 3) * 2 + ksel) ^ kx) << 4));
                mma(s[ks & 1][0], q[ks], b[0], b[1]);
                mma(s[ks & 1][1], q[ks], b[2], b[3]);
            }
            __syncwarp();
            if (lane == 0) mbar_arrive(sb + BAR_EMPTY + 8 * st);
            st += i < KA ? 1 : 2;
            if (st >= NST) { st -= NST; par ^= 1; }
            float sv[2][4];
#pragma unroll
            for (int j = 0; j < 4; j++) { sv[0][j] = s[0][0][j] + s[1][0][j]; sv[1][j] = s[0][1][j] + s[1][1][j]; }
            float t0 = fmaxf(fmaxf(sv[0][0], sv[0][1]), fmaxf(sv[1][0], sv[1][1]));
            float t1 = fmaxf(fmaxf(sv[0][2], sv[0][3]), fmaxf(sv[1][2], sv[1][3]));
            t0 = fmaxf(t0, __shfl_xor_sync(0xffffffffu, t0, 1));
            t1 = fmaxf(t1, __shfl_xor_sync(0xffffffffu, t1, 1));
            t0 = fmaxf(t0, __shfl_xor_sync(0xffffffffu, t0, 2));
            t1 = fmaxf(t1, __shfl_xor_sync(0xffffffffu, t1, 2));
            const uint32_t wm = sb + OFF_WMAX + (i & 1) * 256 + g8 * 16;
            if (quad == 0) { sts32f(wm + warp * 4, t0); sts32f(wm + 128 + warp * 4, t1); }
            bar_sync(2, 128);
            const float4 w0 = lds128f(wm), w1 = lds128f(wm + 128);
            const float n0 = fmaxf(mc0, fmaxf(fmaxf(w0.x, w0.y), fmaxf(w0.z, w0.w)) * C);
            const float n1 = fmaxf(mc1, fmaxf(fmaxf(w1.x, w1.y), fmaxf(w1.z, w1.w)) * C);
            const float a0 = ex2(mc0 - n0), a1 = ex2(mc1 - n1);
            mc0 = n0; mc1 = n1;
            float p[2][4];
#pragma unroll
            for (int j = 0; j < 2; j++) {
                p[j][0] = ex2(fmaf(sv[j][0], C, -n0)); p[j][1] = ex2(fmaf(sv[j][1], C, -n0));
                p[j][2] = ex2(fmaf(sv[j][2], C, -n1)); p[j][3] = ex2(fmaf(sv[j][3], C, -n1));
            }
            l0 = l0 * a0 + ((p[0][0] + p[0][1]) + (p[1][0] + p[1][1]));
            l1 = l1 * a1 + ((p[0][2] + p[0][3]) + (p[1][2] + p[1][3]));
            const int slot = i % NP;
            if (i >= NP) {
                mbar_wait(sb + BAR_PEMPTY + 8 * slot, (i / NP - 1) & 1);
                mbar_wait(sb + BAR_PEMPTY + 8 * (NP + slot), (i / NP - 1) & 1);
            }
            const uint32_t p0 = pack_bf16(p[0][0], p[0][1]), p1 = pack_bf16(p[0][2], p[0][3]), p2 = pack_bf16(p[1][0], p[1][1]),
                           p3 = pack_bf16(p[1][2], p[1][3]);
            asm volatile("st.async.weak.shared::cluster.mbarrier::complete_tx::bytes.v4.b32 [%0], {%1,%2,%3,%4}, [%5];"
                         ::"r"(rp + slot * 2048), "r"(p1), "r"(p0), "r"(p3), "r"(p2), "r"(rfull + 8 * slot) : "memory");
            sts128(sb + OFF_P + slot * 2048 + warp * 512 + lane * 16, p0, p1, p2, p3);
            if (warp == 0 && quad == 0) {
                asm volatile("st.async.weak.shared::cluster.mbarrier::complete_tx::bytes.f32 [%0], %1, [%2];"
                             ::"r"(ra + slot * 64), "f"(a1), "r"(rfull + 8 * slot) : "memory");
                asm volatile("st.async.weak.shared::cluster.mbarrier::complete_tx::bytes.f32 [%0], %1, [%2];"
                             ::"r"(ra + slot * 64 + 32), "f"(a0), "r"(rfull + 8 * slot) : "memory");
                sts32f(sb + OFF_ALPHA + slot * 64 + g8 * 4, a0);
                sts32f(sb + OFF_ALPHA + slot * 64 + 32 + g8 * 4, a1);
            }
            __syncwarp();
            if (lane == 0) mbar_arrive(sb + BAR_PFULL + 8 * slot);
        }
        l0 += __shfl_xor_sync(0xffffffffu, l0, 1);
        l1 += __shfl_xor_sync(0xffffffffu, l1, 1);
        l0 += __shfl_xor_sync(0xffffffffu, l0, 2);
        l1 += __shfl_xor_sync(0xffffffffu, l1, 2);
        if (quad == 0) {
            sts32f(sb + OFF_LSUM + g8 * 16 + warp * 4, l0);
            sts32f(sb + OFF_LSUM + 128 + g8 * 16 + warp * 4, l1);
            if (warp == 0) { sts32f(sb + OFF_MROW + g8 * 4, mc0); sts32f(sb + OFF_MROW + 32 + g8 * 4, mc1); }
        }
        bar_sync(2, 128);
        if (warp == 0) {
            if (lane < 16) {
                const float4 lv = lds128f(sb + OFF_LSUM + lane * 16);
                const float l = (lv.x + lv.y) + (lv.z + lv.w), m = lds32f(sb + OFF_MROW + lane * 4);
                asm volatile("st.async.weak.shared::cluster.mbarrier::complete_tx::bytes.v2.f32 [%0], {%1,%2}, [%3];"
                             ::"r"(mapa(sb + OFF_STAT + lane * 8, rank ^ 1)), "f"(m), "f"(l), "r"(mapa(sb + BAR_STAT, rank ^ 1)) : "memory");
                mbar_wait(sb + BAR_STAT, 0);
                const float pm = lds32f(sb + OFF_STAT + lane * 8), pl = lds32f(sb + OFF_STAT + lane * 8 + 4);
                const float mm = fmaxf(m, pm);
                const float e = ex2(m - mm), pe = ex2(pm - mm);
                const float inv = __fdividef(1.f, rank ? pl * pe + l * e : l * e + pl * pe);
                sts32f(sb + OFF_F + lane * 4, e * inv);
                sts32f(sb + OFF_F + 64 + (lane ^ 8) * 4, pe * inv);
            }
            __syncwarp();
            if (lane == 0) mbar_arrive(sb + BAR_F);
        }
        mbar_wait(sb + BAR_D, 0);
    } else {
        const int w = warp - 4;
        asm volatile("barrier.cluster.wait.acquire.aligned;" ::: "memory");
        const int src = w >> 1, ds = w & 1;
        uint4* const oout = pin(&g_scr.o[(((bh & 7) * 4 + src * 2 + (lane >> 4)) * 4 + rank * 2 + ds) * 128 + (bh >> 3) * 16 + (lane & 15)]);
        const uint32_t pbase = pin(sb + OFF_P + src * NP * 2048 + lane * 16), abase = pin(sb + OFF_ALPHA + src * NP * 64 + g8 * 4);
        const uint32_t pfull = pin(sb + BAR_PFULL + src * NP * 8);
        const uint32_t pempty = src ? mapa(sb + BAR_PEMPTY + 8 * NP, rank ^ 1) : mapa(sb + BAR_PEMPTY, rank);
        float o[4][4], t[2][4][4];
#pragma unroll
        for (int j = 0; j < 16; j++) (&o[0][0])[j] = (&t[0][0][0])[j] = (&t[1][0][0])[j] = 0.f;
        const uint32_t voff = ((rank ^ src) * 64 + (lane & 15)) * 128;
        const int vc = ds * 4 + (lane >> 4), vx = lane & 7;
        const uint32_t v0 = pin(sb + voff + ((vc ^ vx) << 4)), v1 = pin(sb + voff + (((vc + 2) ^ vx) << 4));
        pkt_store(oout, 0, 0, 0, 0, tag ^ 1);
        uint32_t p[4][4], b0[4][4], b1[4][4];
        float a0 = 0.f, a1 = 0.f;
        auto load_v = [&](int st) {
#pragma unroll
            for (int j = 0; j < 4; j++) {
                ldsm4t(b0[j], v0 + st * STAGE + j * 2048);
                ldsm4t(b1[j], v1 + st * STAGE + j * 2048);
            }
        };
        auto next_p = [&](int i) {
            const int slot = i % NP;
            mbar_wait(pfull + 8 * slot, (i / NP) & 1);
#pragma unroll
            for (int j = 0; j < 4; j++) lds128(p[j], pbase + slot * 2048 + j * 512);
            const float n0 = lds32f(abase + slot * 64), n1 = lds32f(abase + slot * 64 + 32);
            __syncwarp();
            if (lane == 0 && i < NT - NP) {
                if (w == 2) mbar_expect_tx(pfull + 8 * slot, 2048 + 64);
                asm volatile("mbarrier.arrive.relaxed.cluster.shared::cluster.b64 _, [%0];"
                             ::"r"(pempty + 8 * slot + ((p[3][3] | __float_as_uint(n1)) & zero)) : "memory");
            }
#pragma unroll
            for (int j = 0; j < 4; j++) {
                o[j][0] = fmaf(o[j][0], a0, t[0][j][0] + t[1][j][0]); o[j][1] = fmaf(o[j][1], a0, t[0][j][1] + t[1][j][1]);
                o[j][2] = fmaf(o[j][2], a1, t[0][j][2] + t[1][j][2]); o[j][3] = fmaf(o[j][3], a1, t[0][j][3] + t[1][j][3]);
            }
            a0 = n0; a1 = n1;
        };
        auto pv = [&]() {
#pragma unroll
            for (int j = 0; j < 16; j++) (&t[0][0][0])[j] = (&t[1][0][0])[j] = 0.f;
#pragma unroll
            for (int j = 0; j < 4; j++) {
                mma(t[j & 1][0], p[j], b0[j][0], b0[j][1]);
                mma(t[j & 1][1], p[j], b0[j][2], b0[j][3]);
                mma(t[j & 1][2], p[j], b1[j][0], b1[j][1]);
                mma(t[j & 1][3], p[j], b1[j][2], b1[j][3]);
            }
        };
        int st = KA + 1;
        uint32_t par = 0;
#pragma unroll 1
        for (int i = 0; i < NT - 1; i++) {
            mbar_wait(sb + BAR_FULL + 8 * st, par);
            load_v(st);
            next_p(i);
            pv();
            __syncwarp();
            if (lane == 0) mbar_arrive(sb + BAR_EMPTY + 8 * st);
            st += i < NT - KA - 1 ? 2 : 1;
            if (st >= NST) { st -= NST; par ^= 1; }
        }
        constexpr int LST = (2 * NT - 1) % NST, LPAR = ((2 * NT - 1) / NST) & 1;
        const bool landed = mbar_test(sb + BAR_FULL + 8 * LST, LPAR);
        if (landed) load_v(LST);
        next_p(NT - 1);
        mbar_wait(sb + BAR_F, 0);
        const float f0 = lds32f(sb + OFF_F + src * 64 + g8 * 4), f1 = lds32f(sb + OFF_F + src * 64 + 32 + g8 * 4);
        a0 *= f0; a1 *= f1;
#pragma unroll
        for (int j = 0; j < 4; j++) {
            o[j][0] *= a0; o[j][1] *= a0; o[j][2] *= a1; o[j][3] *= a1;
            asm volatile("" : "+f"(o[j][0]), "+f"(o[j][1]), "+f"(o[j][2]), "+f"(o[j][3]));
        }
        if (!landed) {
            mbar_wait(sb + BAR_FULL + 8 * LST, LPAR);
            load_v(LST);
        }
        pv();
#pragma unroll
        for (int j = 0; j < 4; j++) {
            o[j][0] = fmaf(t[0][j][0] + t[1][j][0], f0, o[j][0]); o[j][1] = fmaf(t[0][j][1] + t[1][j][1], f0, o[j][1]);
            o[j][2] = fmaf(t[0][j][2] + t[1][j][2], f1, o[j][2]); o[j][3] = fmaf(t[0][j][3] + t[1][j][3], f1, o[j][3]);
        }
        {
            const uint32_t mine = sb + OFF_MERGE + w * 1024 + lane * 16, theirs = sb + OFF_MERGE + (w ^ 2) * 1024 + lane * 16;
            sts128f(theirs, o[0][2], o[0][3], o[1][2], o[1][3]);
            sts128f(theirs + 512, o[2][2], o[2][3], o[3][2], o[3][3]);
            bar_sync(5 + ds, 64);
            const float4 r0 = lds128f(mine), r1 = lds128f(mine + 512);
            pkt_store(oout, pack_bf16(o[0][0] + r0.x, o[0][1] + r0.y), pack_bf16(o[1][0] + r0.z, o[1][1] + r0.w),
                      pack_bf16(o[2][0] + r1.x, o[2][1] + r1.y), pack_bf16(o[3][0] + r1.z, o[3][1] + r1.w), tag);
        }
        if (lane == 0) mbar_arrive(sb + BAR_D);
    }

    {
        uint32_t a[8][2][4];
        const int kr = (lane >> 4) * 8 + (lane & 7);
        const int wc = (lane >> 3) & 1, wx = (kr >> 1) & 3;
        const uint32_t wb0 = pin(sb + OFF_WO + (g * 128 + kr) * 64 + ((wc ^ wx) << 4));
        const uint32_t wb1 = pin(sb + OFF_WO + (g * 128 + kr) * 64 + (((wc + 2) ^ wx) << 4));
        const uint32_t red = pin(sb + OFF_PRED + rh * 8192 + lane * 16);
        const uint32_t rw = pin(red + g * 512), rr = pin(red + (g & 1) * 4096 + (g >> 1) * 2048);
        const uint32_t wobar = sb + BAR_WO + 8 * g;
        constexpr uint32_t wopar = 0;
        auto wo_within = [&](uint32_t clks) {
            uint32_t c0, c1;
            bool in;
            asm volatile("mov.u32 %0, %%clock;" : "=r"(c0));
            do {
                in = mbar_test(wobar, wopar);
                asm volatile("mov.u32 %0, %%clock;" : "=r"(c1));
            } while (!in && c1 - c0 < clks);
            return in;
        };
        Pkt v[8];
        const bool in0 = wo_within(O_DELAY);
        pkt_issue<8, 4, 128, 32>(v, oin);
        if (!in0) {
#pragma unroll 1
            for (int it = 0; !wo_within(O_PERIOD); it++) {
                uint32_t b[8];
#pragma unroll
                for (int i = 0; i < 8; i++) b[i] = v[i].bad(tag);
                if (it > (1 << 16)) __trap();
#pragma unroll
                for (int i = 0; i < 8; i++) pkt_reload(v[i], oin + (i >> 2) * 32 + (i & 3) * 128, b[i]);
            }
        }
#pragma unroll
        for (int ks = 0; ks < 8; ks++) {
            ldsm4t(a[ks][0], wb0 + ks * 1024);
            ldsm4t(a[ks][1], wb1 + ks * 1024);
        }
        pkt_poll<8, 4, 128, 32>(v, oin, tag | (a[7][1][3] & zero));
        float c[2][2][2][4];
#pragma unroll
        for (int j = 0; j < 32; j++) (&c[0][0][0][0])[j] = 0.f;
#pragma unroll
        for (int dq = 0; dq < 4; dq++)
#pragma unroll
            for (int t = 0; t < 2; t++) {
                mma(c[t][0][0], a[2 * dq][0], v[t * 4 + dq].w0(), v[t * 4 + dq].w1());
                mma(c[t][1][0], a[2 * dq][1], v[t * 4 + dq].w0(), v[t * 4 + dq].w1());
                mma(c[t][0][1], a[2 * dq + 1][0], v[t * 4 + dq].w2(), v[t * 4 + dq].w3());
                mma(c[t][1][1], a[2 * dq + 1][1], v[t * 4 + dq].w2(), v[t * 4 + dq].w3());
            }
#pragma unroll
        for (int t = 0; t < 2; t++)
#pragma unroll
            for (int mt = 0; mt < 2; mt++)
                sts128f(rw + t * 4096 + mt * 2048, c[t][mt][0][0] + c[t][mt][1][0], c[t][mt][0][1] + c[t][mt][1][1],
                        c[t][mt][0][2] + c[t][mt][1][2], c[t][mt][0][3] + c[t][mt][1][3]);
        bar_sync(3 + rh, 128);
        const float4 s0 = lds128f(rr), s1 = lds128f(rr + 512), s2 = lds128f(rr + 1024), s3 = lds128f(rr + 1536);
        pkt_store(pout, __float_as_uint((s0.x + s1.x) + (s2.x + s3.x)), __float_as_uint((s0.y + s1.y) + (s2.y + s3.y)),
                  __float_as_uint((s0.z + s1.z) + (s2.z + s3.z)), __float_as_uint((s0.w + s1.w) + (s2.w + s3.w)), tag);
    }

    {
        if (warp < 4) {
            Pkt v[2];
            spin(P_DELAY);
            pkt_load(v[0], pin_);
            pkt_load(v[1], pin_ + 128);
#pragma unroll 1
            for (int it = 0;; it++) {
                const uint32_t b0 = v[0].bad(tag), b1 = v[1].bad(tag);
                if (!any_bit0(or3(b0, b1, 0u))) break;
                pkt_reload(v[0], pin_, b0);
                pkt_reload(v[1], pin_ + 128, b1);
                if (it > (1 << 20)) __trap();
            }
            const float e0 = __uint_as_float(v[0].w0()) + __uint_as_float(v[1].w0()), e1 = __uint_as_float(v[0].w1()) + __uint_as_float(v[1].w1());
            const float e2 = __uint_as_float(v[0].w2()) + __uint_as_float(v[1].w2()), e3 = __uint_as_float(v[0].w3()) + __uint_as_float(v[1].w3());
            const bool hi = lane & 8, hi2 = lane & 16;
            const float k0 = (hi ? e1 : e0) + __shfl_xor_sync(0xffffffffu, hi ? e0 : e1, 8);
            const float k1 = (hi ? e3 : e2) + __shfl_xor_sync(0xffffffffu, hi ? e2 : e3, 8);
            const uint32_t res = pack_bf16((hi2 ? k1 : k0) + __shfl_xor_sync(0xffffffffu, hi2 ? k0 : k1, 16), 0.f);
            asm volatile("st.global.u16 [%0], %1;" ::"l"(optr), "h"((uint16_t)res) : "memory");
        }
        if ((cta | warp | lane) == 0)
            asm volatile("st.relaxed.gpu.global.u32 [%0], %1;" ::"l"(&g_scr.epoch), "r"(epoch + 1) : "memory");
    }
}

__global__ void fb_proj(const __nv_bfloat16* a_bf, const float* a_f, const __nv_bfloat16* w, int K, int N, float* o_f,
                        __nv_bfloat16* o_bf) {
    const int c = blockIdx.x * blockDim.x + threadIdx.x, r = blockIdx.y;
    float s = 0.f;
    for (int k = 0; k < K; k++) s += (a_bf ? __bfloat162float(a_bf[r * K + k]) : a_f[r * K + k]) * __bfloat162float(w[k * N + c]);
    if (o_bf) o_bf[r * N + c] = __float2bfloat16(s);
    else o_f[r * N + c] = __bfloat162float(__float2bfloat16(s));
}
__global__ void fb_attn(const __nv_bfloat16* kc, const __nv_bfloat16* vc) {
    __shared__ float sc[2048], red[128];
    const int r = blockIdx.x, hq = blockIdx.y, t = threadIdx.x;
    const size_t base = (size_t)((r >> 2) * 8 + (hq >> 2)) * 2048 * 128;
    float m = -INFINITY, l = 0.f, acc = 0.f;
    for (int j = t; j < 2048; j += 128) {
        float s = 0.f;
        for (int d = 0; d < 128; d++) s += g_scr.fq[r * 4096 + hq * 128 + d] * __bfloat162float(kc[base + j * 128 + d]);
        sc[j] = s * 0.08838834764831845f;
        m = fmaxf(m, sc[j]);
    }
    red[t] = m;
    __syncthreads();
    for (int i = 0; i < 128; i++) m = fmaxf(m, red[i]);
    for (int j = t; j < 2048; j += 128) sc[j] = __expf(sc[j] - m);
    __syncthreads();
    for (int j = 0; j < 2048; j++) {
        l += sc[j];
        acc += sc[j] * __bfloat162float(vc[base + j * 128 + t]);
    }
    g_scr.fo[r * 4096 + hq * 128 + t] = __bfloat162float(__float2bfloat16(acc / l));
}

typedef CUresult (*EncodeFn)(CUtensorMap*, CUtensorMapDataType, cuuint32_t, void*, const cuuint64_t*, const cuuint64_t*,
                             const cuuint32_t*, const cuuint32_t*, CUtensorMapInterleave, CUtensorMapSwizzle,
                             CUtensorMapL2promotion, CUtensorMapFloatOOBfill);

static void encode(EncodeFn fn, CUtensorMap* m, void* p, int rank, const cuuint64_t* dims, const cuuint64_t* strides,
                   const cuuint32_t* box, CUtensorMapSwizzle sw) {
    const cuuint32_t es[3] = {1, 1, 1};
    fn(m, CU_TENSOR_MAP_DATA_TYPE_BFLOAT16, rank, p, dims, strides, box, es, CU_TENSOR_MAP_INTERLEAVE_NONE, sw,
       CU_TENSOR_MAP_L2_PROMOTION_L2_256B, CU_TENSOR_MAP_FLOAT_OOB_FILL_NONE);
}

}

extern "C" void kernel_launch(void* const* d_in, const int* in_sizes, int n_in, void* d_out, int out_size) {
    using namespace gqa;
    static EncodeFn fn = nullptr;
    static uint32_t slot_ns = SLOT_NS;
    static bool fits = false;
    if (!fn) {
        int dev = 0, khz = 0, bits = 0;
        cudaGetDevice(&dev);
        cudaDeviceGetAttribute(&khz, cudaDevAttrMemoryClockRate, dev);
        cudaDeviceGetAttribute(&bits, cudaDevAttrGlobalMemoryBusWidth, dev);
        if (khz > 0 && bits > 0) slot_ns = (uint32_t)((double)NCTA * STAGE / (0.955 * 2.0 * khz * 1e-6 * (bits / 8)));
        void* p = nullptr;
        cudaDriverEntryPointQueryResult qr;
        cudaGetDriverEntryPoint("cuTensorMapEncodeTiled", &p, cudaEnableDefault, &qr);
        fn = (EncodeFn)p;
        cudaFuncSetAttribute(gqa_kernel, cudaFuncAttributeMaxDynamicSharedMemorySize, SMEM_BYTES);
        cudaLaunchConfig_t cfg = {};
        cfg.gridDim = dim3(NCTA);
        cfg.blockDim = dim3(288);
        cfg.dynamicSmemBytes = SMEM_BYTES;
        int clusters = 0;
        fits = cudaOccupancyMaxActiveClusters(&clusters, gqa_kernel, &cfg) == cudaSuccess && clusters >= NCTA / 2;
    }
    if (!fits) {
        Scratch* scr = nullptr;
        cudaGetSymbolAddress((void**)&scr, g_scr);
        float *fq = scr->fq, *fo = scr->fo;
        fb_proj<<<dim3(16, 32), 256, 0, cudaStreamPerThread>>>((const __nv_bfloat16*)d_in[0], nullptr, (const __nv_bfloat16*)d_in[3], 512,
                                                               4096, fq, nullptr);
        fb_attn<<<dim3(32, 32), 128, 0, cudaStreamPerThread>>>((const __nv_bfloat16*)d_in[1], (const __nv_bfloat16*)d_in[2]);
        fb_proj<<<dim3(2, 32), 256, 0, cudaStreamPerThread>>>(nullptr, fo, (const __nv_bfloat16*)d_in[4], 4096, 512, nullptr,
                                                              (__nv_bfloat16*)d_out);
        return;
    }
    CUtensorMap tmK, tmV, tmX, tmWq, tmWo;
    {
        const cuuint64_t dims[3] = {64, 8 * 8 * 2048, 2}, str[2] = {256, 128};
        const cuuint32_t box[3] = {64, 64, 2};
        encode(fn, &tmK, d_in[1], 3, dims, str, box, CU_TENSOR_MAP_SWIZZLE_128B);
        const cuuint64_t dv[2] = {128, 8 * 8 * 2048}, sv[1] = {256};
        const cuuint32_t bv[2] = {64, 128};
        encode(fn, &tmV, d_in[2], 2, dv, sv, bv, CU_TENSOR_MAP_SWIZZLE_128B);
    }
    {
        const cuuint64_t dims[3] = {64, 32, 8}, str[2] = {1024, 128};
        const cuuint32_t box[3] = {64, 32, 8};
        encode(fn, &tmX, d_in[0], 3, dims, str, box, CU_TENSOR_MAP_SWIZZLE_128B);
    }
    {
        const cuuint64_t dq[2] = {4096, 512}, sq[1] = {8192}, dw[2] = {512, 4096}, sw[1] = {1024};
        const cuuint32_t box[2] = {32, 256};
        encode(fn, &tmWq, d_in[3], 2, dq, sq, box, CU_TENSOR_MAP_SWIZZLE_64B);
        const cuuint32_t boxo[2] = {32, 128};
        encode(fn, &tmWo, d_in[4], 2, dw, sw, boxo, CU_TENSOR_MAP_SWIZZLE_64B);
    }
    gqa_kernel<<<NCTA, 288, SMEM_BYTES, cudaStreamPerThread>>>(Ptrs{{(const uint8_t*)d_in[3], nullptr}}, (__nv_bfloat16*)d_out, slot_ns, 0u, tmK, tmV, tmX,
                                                               tmWq, tmWo);
}
```

```cpp
#include <cuda_runtime.h>
#include <cuda_bf16.h>
#include <cuda.h>
#include <stdint.h>

namespace gqa {

constexpr int PA_NS = 2780;
constexpr int SLOT_NS = 655;
constexpr int WO_SLOT = 2880;
constexpr int WO_STEP = 65;
constexpr int Q_DELAY_NS = 1000;
constexpr int O_DELAY = 1000;
constexpr int O_PERIOD = 350;
constexpr int PF_BYTES = 8192;

constexpr int NCTA = 128;
constexpr int NT = 16;
constexpr int NST = 13;
constexpr int NST0 = 10;
constexpr int WIN0 = 3;
constexpr int WIN = 8;
constexpr int WSW = 8;
constexpr int KA = 2;
constexpr int NP = 4;
constexpr int STAGE = 16384;

constexpr int OFF_WQ = NST0 * STAGE;
constexpr int OFF_X = OFF_WQ + 32768;
constexpr int OFF_QRED = OFF_X;
constexpr int OFF_WO = ((2 * NT) % NST) * STAGE;
constexpr int OFF_P = NST * STAGE;
constexpr int OFF_MERGE = (((2 * NT) % NST) + 3) * STAGE;
constexpr int OFF_ALPHA = (NST + 1) * STAGE + 512;
constexpr int OFF_WMAX = OFF_ALPHA + 2 * NP * 64;
constexpr int OFF_LSUM = OFF_WMAX + 512;
constexpr int OFF_MROW = OFF_LSUM + 256;
constexpr int OFF_STAT = OFF_MROW + 64;
constexpr int OFF_F = OFF_STAT + 128;
constexpr int OFF_PRED = (((2 * NT) % NST) + 2) * STAGE;
constexpr int OFF_BAR = (NST + 1) * STAGE;
constexpr int BAR_FULL = OFF_BAR;
constexpr int BAR_EMPTY = BAR_FULL + 8 * NST;
constexpr int BAR_PFULL = BAR_EMPTY + 8 * NST;
constexpr int BAR_PEMPTY = BAR_PFULL + 16 * NP;
constexpr int BAR_W = BAR_PEMPTY + 16 * NP;
constexpr int BAR_STAT = BAR_W + 8;
constexpr int BAR_F = BAR_STAT + 8;
constexpr int BAR_D = BAR_F + 8;
constexpr int BAR_WO = BAR_D + 8;
constexpr int SMEM_BYTES = OFF_F + 128;
static_assert(2 * NP * 2048 <= STAGE, "P slots overflow");
static_assert(BAR_WO + 32 <= OFF_ALPHA, "barriers overflow");
static_assert((2 * NT) % NST + 3 < NST, "wo / partial slots must not wrap");
static_assert(SMEM_BYTES <= 232448, "too much shared memory");

struct __align__(1024) Scratch {
    uint4 q[32 * 4 * 8 * 16];
    uint4 o[32 * 4 * 8 * 16];
    unsigned ticket;
    unsigned pad[31];
    unsigned zeroed[16 * 32];
    float fq[32 * 4096], fo[32 * 4096];
};
__device__ Scratch g_scr;

__device__ __forceinline__ void mbar_init(uint32_t bar, uint32_t cnt) {
    asm volatile("mbarrier.init.shared::cta.b64 [%0], %1;" ::"r"(bar), "r"(cnt) : "memory");
}
__device__ __forceinline__ void mbar_expect_tx(uint32_t bar, uint32_t bytes) {
    asm volatile("mbarrier.arrive.expect_tx.shared::cta.b64 _, [%0], %1;" ::"r"(bar), "r"(bytes) : "memory");
}
__device__ __forceinline__ void mbar_arrive(uint32_t bar) {
    asm volatile("mbarrier.arrive.shared::cta.b64 _, [%0];" ::"r"(bar) : "memory");
}
__device__ __forceinline__ bool mbar_try(uint32_t bar, uint32_t parity) {
    uint32_t ok;
    asm volatile("{\n.reg .pred p;\nmbarrier.try_wait.parity.shared::cta.b64 p, [%1], %2;\nselp.u32 %0, 1, 0, p;\n}"
                 : "=r"(ok) : "r"(bar), "r"(parity) : "memory");
    return ok;
}
__device__ __forceinline__ bool mbar_test(uint32_t bar, uint32_t parity) {
    uint32_t ok;
    asm volatile("{\n.reg .pred p;\nmbarrier.test_wait.parity.shared::cta.b64 p, [%1], %2;\nselp.u32 %0, 1, 0, p;\n}"
                 : "=r"(ok) : "r"(bar), "r"(parity) : "memory");
    return ok;
}
__device__ __forceinline__ void mbar_wait(uint32_t bar, uint32_t parity) {
#pragma unroll 1
    for (int i = 0; !mbar_try(bar, parity); i++)
        if (i > (1 << 20)) __trap();
}
__device__ __forceinline__ void tma2d(uint32_t dst, const CUtensorMap* m, int c0, int c1, uint32_t bar) {
    asm volatile("cp.async.bulk.tensor.2d.shared::cluster.global.mbarrier::complete_tx::bytes [%0], [%1, {%3, %4}], [%2];"
                 ::"r"(dst), "l"(m), "r"(bar), "r"(c0), "r"(c1) : "memory");
}
__device__ __forceinline__ void tma3d(uint32_t dst, const CUtensorMap* m, int c0, int c1, int c2, uint32_t bar) {
    asm volatile("cp.async.bulk.tensor.3d.shared::cluster.global.mbarrier::complete_tx::bytes [%0], [%1, {%3, %4, %5}], [%2];"
                 ::"r"(dst), "l"(m), "r"(bar), "r"(c0), "r"(c1), "r"(c2) : "memory");
}
__device__ __forceinline__ void tma2d_hint(uint32_t dst, const CUtensorMap* m, int c0, int c1, uint32_t bar, uint64_t pol) {
    asm volatile("cp.async.bulk.tensor.2d.shared::cluster.global.mbarrier::complete_tx::bytes.L2::cache_hint [%0], [%1, {%3, %4}], [%2], %5;"
                 ::"r"(dst), "l"(m), "r"(bar), "r"(c0), "r"(c1), "l"(pol) : "memory");
}
__device__ __forceinline__ uint32_t mapa(uint32_t addr, uint32_t cta_rank) {
    uint32_t r;
    asm("mapa.shared::cluster.u32 %0, %1, %2;" : "=r"(r) : "r"(addr), "r"(cta_rank));
    return r;
}
__device__ __forceinline__ void tma3d_hint(uint32_t dst, const CUtensorMap* m, int c0, int c1, int c2, uint32_t bar, uint64_t pol) {
    asm volatile("cp.async.bulk.tensor.3d.shared::cluster.global.mbarrier::complete_tx::bytes.L2::cache_hint [%0], [%1, {%3, %4, %5}], [%2], %6;"
                 ::"r"(dst), "l"(m), "r"(bar), "r"(c0), "r"(c1), "r"(c2), "l"(pol) : "memory");
}
__device__ __forceinline__ void ldsm4(uint32_t (&r)[4], uint32_t addr) {
    asm volatile("ldmatrix.sync.aligned.m8n8.x4.shared.b16 {%0,%1,%2,%3}, [%4];"
                 : "=r"(r[0]), "=r"(r[1]), "=r"(r[2]), "=r"(r[3]) : "r"(addr) : "memory");
}
__device__ __forceinline__ void ldsm4t(uint32_t (&r)[4], uint32_t addr) {
    asm volatile("ldmatrix.sync.aligned.m8n8.x4.trans.shared.b16 {%0,%1,%2,%3}, [%4];"
                 : "=r"(r[0]), "=r"(r[1]), "=r"(r[2]), "=r"(r[3]) : "r"(addr) : "memory");
}
__device__ __forceinline__ void mma(float (&c)[4], const uint32_t (&a)[4], uint32_t b0, uint32_t b1) {
    asm volatile("mma.sync.aligned.m16n8k16.row.col.f32.bf16.bf16.f32 {%0,%1,%2,%3}, {%4,%5,%6,%7}, {%8,%9}, {%0,%1,%2,%3};"
                 : "+f"(c[0]), "+f"(c[1]), "+f"(c[2]), "+f"(c[3])
                 : "r"(a[0]), "r"(a[1]), "r"(a[2]), "r"(a[3]), "r"(b0), "r"(b1));
}
__device__ __forceinline__ uint32_t pack_bf16(float lo, float hi) {
    uint32_t r;
    asm("cvt.rn.bf16x2.f32 %0, %1, %2;" : "=r"(r) : "f"(hi), "f"(lo));
    return r;
}
__device__ __forceinline__ float ex2(float x) {
    float y;
    asm("ex2.approx.ftz.f32 %0, %1;" : "=f"(y) : "f"(x));
    return y;
}
__device__ __forceinline__ void sts128(uint32_t addr, uint32_t a, uint32_t b, uint32_t c, uint32_t d) {
    asm volatile("st.shared.v4.b32 [%0], {%1,%2,%3,%4};" ::"r"(addr), "r"(a), "r"(b), "r"(c), "r"(d) : "memory");
}
__device__ __forceinline__ void sts128f(uint32_t addr, float a, float b, float c, float d) {
    asm volatile("st.shared.v4.f32 [%0], {%1,%2,%3,%4};" ::"r"(addr), "f"(a), "f"(b), "f"(c), "f"(d) : "memory");
}
__device__ __forceinline__ void sts32f(uint32_t addr, float a) {
    asm volatile("st.shared.f32 [%0], %1;" ::"r"(addr), "f"(a) : "memory");
}
__device__ __forceinline__ void lds128(uint32_t (&r)[4], uint32_t addr) {
    asm volatile("ld.shared.v4.b32 {%0,%1,%2,%3}, [%4];" : "=r"(r[0]), "=r"(r[1]), "=r"(r[2]), "=r"(r[3]) : "r"(addr) : "memory");
}
__device__ __forceinline__ float4 lds128f(uint32_t addr) {
    float4 v;
    asm volatile("ld.shared.v4.f32 {%0,%1,%2,%3}, [%4];" : "=f"(v.x), "=f"(v.y), "=f"(v.z), "=f"(v.w) : "r"(addr) : "memory");
    return v;
}
__device__ __forceinline__ float lds32f(uint32_t addr) {
    float v;
    asm volatile("ld.shared.f32 %0, [%1];" : "=f"(v) : "r"(addr) : "memory");
    return v;
}
__device__ __forceinline__ void bar_sync(int id, int n) { asm volatile("bar.sync %0, %1;" ::"r"(id), "r"(n) : "memory"); }
template <typename T> __device__ __forceinline__ T* pin(T* p) { asm volatile("" : "+l"(p)); return p; }
__device__ __forceinline__ uint32_t pin(uint32_t v) { asm volatile("" : "+r"(v)); return v; }

struct Pkt {
    uint64_t lo, hi;
    __device__ __forceinline__ uint32_t w0() const { return (uint32_t)lo; }
    __device__ __forceinline__ uint32_t w1() const { return (uint32_t)(lo >> 32); }
    __device__ __forceinline__ uint32_t w2() const { return (uint32_t)hi; }
    __device__ __forceinline__ uint32_t w3() const { return (uint32_t)(hi >> 32); }
    __device__ __forceinline__ uint32_t bad(uint32_t tag) const {
        uint32_t r;
        asm("lop3.b32 %0, %1, %2, %3, 0x7E;" : "=r"(r) : "r"(w0()), "r"(w2()), "r"(tag));
        return r;
    }
};
__device__ __forceinline__ void pkt_store(uint4* p, uint32_t a, uint32_t b, uint32_t c, uint32_t d, uint32_t tag) {
    a = (a & ~1u) | tag;
    c = (c & ~1u) | tag;
    asm volatile("{\n.reg .b64 lo, hi;\nmov.b64 lo, {%1,%2};\nmov.b64 hi, {%3,%4};\n"
                 "st.relaxed.gpu.global.v2.b64 [%0], {lo, hi};\n}" ::"l"(p), "r"(a), "r"(b), "r"(c), "r"(d) : "memory");
}
__device__ __forceinline__ uint32_t pack_bf16_tagged(float lo, float hi, uint32_t tag) {
    uint32_t r = pack_bf16(lo, hi);
    if ((r ^ tag) & 1u) {
        const uint32_t mag = r & 0x7fffu;
        const bool up = mag == 0 || (fabsf(lo) > __uint_as_float(mag << 16) && mag < 0x7f7fu);
        r += up ? 1u : 0xffffffffu;
    }
    return r;
}
__device__ __forceinline__ void pkt_load(Pkt& v, const uint4* p) {
    asm volatile("ld.relaxed.gpu.global.v2.b64 {%0, %1}, [%2];" : "=l"(v.lo), "=l"(v.hi) : "l"(p) : "memory");
}
__device__ __forceinline__ void pkt_reload(Pkt& v, const uint4* p, uint32_t bad) {
    asm volatile("{\n.reg .pred p;\n.reg .b32 t;\nand.b32 t, %3, 1;\nsetp.ne.u32 p, t, 0;\n"
                 "@p ld.relaxed.gpu.global.v2.b64 {%0, %1}, [%2];\n}"
                 : "+l"(v.lo), "+l"(v.hi) : "l"(p), "r"(bad) : "memory");
}
__device__ __forceinline__ uint32_t or3(uint32_t a, uint32_t b, uint32_t c) {
    uint32_t r;
    asm("lop3.b32 %0, %1, %2, %3, 0xFE;" : "=r"(r) : "r"(a), "r"(b), "r"(c));
    return r;
}
__device__ __forceinline__ bool any_bit0(uint32_t x) {
    uint32_t r;
    asm volatile("{\n.reg .pred p, q;\n.reg .b32 t;\nand.b32 t, %1, 1;\nsetp.ne.u32 p, t, 0;\nvote.sync.any.pred q, p, 0xffffffff;\n"
                 "selp.u32 %0, 1, 0, q;\n}" : "=r"(r) : "r"(x));
    return r;
}
template <int N, int N0, int S0, int S1>
__device__ __forceinline__ void pkt_issue(Pkt (&v)[N], const uint4* p) {
#pragma unroll
    for (int i = 0; i < N; i++) pkt_load(v[i], p + (i / N0) * S1 + (i % N0) * S0);
}
template <int N, int N0, int S0, int S1>
__device__ __forceinline__ void pkt_poll(Pkt (&v)[N], const uint4* p, uint32_t tag) {
    static_assert(N == 1 || N == 8, "");
#pragma unroll 1
    for (int it = 0;; it++) {
        uint32_t b[N];
#pragma unroll
        for (int i = 0; i < N; i++) b[i] = v[i].bad(tag);
        uint32_t bad = b[0];
        if (N == 8) bad = or3(or3(b[0], b[1 % N], b[2 % N]), or3(b[3 % N], b[4 % N], b[5 % N]), or3(b[6 % N], b[7 % N], 0u));
        if (!any_bit0(bad)) break;
#pragma unroll
        for (int i = 0; i < N; i++) pkt_reload(v[i], p + (i / N0) * S1 + (i % N0) * S0, b[i]);
        if (it > (1 << 20)) __trap();
    }
}

__device__ __forceinline__ uint32_t now_ns() {
    uint32_t t;
    asm volatile("mov.u32 %0, %%globaltimer_lo;" : "=r"(t));
    return t;
}
__device__ __forceinline__ void wait_until(uint32_t t) {
#pragma unroll 1
    for (int i = 0; (int)(now_ns() - t) < 0 && i < (1 << 16); i++) {}
}

struct Ptrs { const uint8_t* p[2]; };

__global__ void __cluster_dims__(2, 1, 1) __launch_bounds__(288, 1)
gqa_kernel(const __grid_constant__ Ptrs ptrs, __nv_bfloat16* __restrict__ out, uint32_t slot_ns, uint32_t zero,
           const __grid_constant__ CUtensorMap tmK, const __grid_constant__ CUtensorMap tmV,
           const __grid_constant__ CUtensorMap tmX, const __grid_constant__ CUtensorMap tmWq,
           const __grid_constant__ CUtensorMap tmWo) {
    const uint32_t tstart = now_ns();
    if (threadIdx.x == 32)
        asm volatile("cp.async.bulk.prefetch.L2.global [%0], %1;" ::"l"(ptrs.p[blockIdx.x >> 10] + blockIdx.x * PF_BYTES), "r"(PF_BYTES)
                     : "memory");
    extern __shared__ __align__(1024) uint8_t smem_raw[];
    const uint32_t sb = pin((uint32_t)__cvta_generic_to_shared(smem_raw));
    if (threadIdx.x == 0) {
        mbar_init(sb + BAR_W, 1);
        asm volatile("fence.mbarrier_init.release.cluster;" ::: "memory");
        mbar_expect_tx(sb + BAR_W, 65536);
        tma2d(sb + OFF_WQ, &tmWq, blockIdx.x * 32, 0, sb + BAR_W);
        tma2d(sb + OFF_WQ + 16384, &tmWq, blockIdx.x * 32, 256, sb + BAR_W);
        tma3d(sb + OFF_X, &tmX, 0, 0, 0, sb + BAR_W);
    }
    const int warp = __shfl_sync(0xffffffffu, threadIdx.x >> 5, 0), lane = pin(threadIdx.x & 31);
    const int cta = pin(blockIdx.x), rank = cta & 1, bh = cta >> 1;

    if (warp == 8) {
        const int row0 = bh * 2048 + rank * 64;
        uint64_t pol;
        asm volatile("createpolicy.fractional.L2::evict_first.b64 %0, 1.0;" : "=l"(pol));
        auto issue = [&](int n) {
            const bool isv = n >= 2 * NT - KA || (n >= KA && ((n - KA) & 1));
            const int t = n < KA ? n : n >= 2 * NT - KA ? n - NT : isv ? (n - KA) >> 1 : (n + KA) >> 1;
            const int st = n % NST;
            if (isv) tma2d_hint(sb + st * STAGE, &tmV, rank * 64, bh * 2048 + t * 128, sb + BAR_FULL + 8 * st, pol);
            else tma3d_hint(sb + st * STAGE, &tmK, 0, row0 + t * 128, 0, sb + BAR_FULL + 8 * st, pol);
        };
        if (lane == 0) {
            if (sb & 1023) __trap();
#pragma unroll
            for (int i = 0; i < WIN0; i++) mbar_init(sb + BAR_FULL + 8 * i, 1);
            asm volatile("fence.mbarrier_init.release.cluster;" ::: "memory");
#pragma unroll
            for (int n = 0; n < WIN0; n++) {
                mbar_expect_tx(sb + BAR_FULL + 8 * n, STAGE);
                issue(n);
            }
            for (int i = WIN0; i < NST; i++) mbar_init(sb + BAR_FULL + 8 * i, 1);
            for (int i = 0; i < NST; i++) mbar_init(sb + BAR_EMPTY + 8 * i, 4);
            for (int i = 0; i < NP; i++) {
                mbar_init(sb + BAR_PFULL + 8 * i, 4);
                mbar_init(sb + BAR_PFULL + 8 * (NP + i), 1);
                mbar_expect_tx(sb + BAR_PFULL + 8 * (NP + i), 2048 + 64);
                mbar_init(sb + BAR_PEMPTY + 8 * i, 2);
                mbar_init(sb + BAR_PEMPTY + 8 * (NP + i), 2);
            }
            mbar_init(sb + BAR_STAT, 1);
            mbar_init(sb + BAR_F, 1);
            mbar_init(sb + BAR_D, 4);
            mbar_expect_tx(sb + BAR_STAT, 128);
            for (int i = 0; i < 4; i++) {
                mbar_init(sb + BAR_WO + 8 * i, 1);
                mbar_expect_tx(sb + BAR_WO + 8 * i, 8192);
            }
            asm volatile("fence.mbarrier_init.release.cluster;" ::: "memory");
            asm volatile("prefetch.tensormap [%0];" ::"l"(&tmWo) : "memory");
        }
        __syncwarp();
        asm volatile("bar.arrive 0, 288;" ::: "memory");
        asm volatile("barrier.cluster.arrive.relaxed.aligned;" ::: "memory");
        if (lane == 0) {
            auto wait_free = [&](int n) {
                const int st = n % NST, k = n / NST;
                if (st >= NST0) mbar_wait(sb + BAR_EMPTY + 8 * st, k & 1);
                else if (k) mbar_wait(sb + BAR_EMPTY + 8 * st, (k - 1) & 1);
            };
            const uint32_t t3 = tstart + PA_NS;
#pragma unroll
            for (int n = WIN0; n < 2 * NT; n++) {
                wait_free(n);
                mbar_expect_tx(sb + BAR_FULL + 8 * (n % NST), STAGE);
                if (n < WSW || n >= WSW + WIN - WIN0) {
                    const int d = n - (n < WSW ? WIN0 : WIN);
                    mbar_wait(sb + BAR_FULL + 8 * (d % NST), (d / NST) & 1);
                }
                if (n >= WSW) wait_until(t3 + (n - 3) * slot_ns);
                issue(n);
            }
            wait_free(2 * NT); wait_free(2 * NT + 1); wait_free(2 * NT + 2);
#pragma unroll
            for (int g = 0; g < 4; g++) {
                wait_until(t3 + (WO_SLOT + g * WO_STEP) * slot_ns / 100);
                tma2d(sb + OFF_WO + g * 8192, &tmWo, (cta & 15) * 32, (cta >> 4) * 512 + g * 128, sb + BAR_WO + 8 * g);
            }
        }
        return;
    }

    unsigned epoch;
    asm volatile("ld.relaxed.gpu.global.u32 %0, [%1];" : "=r"(epoch) : "l"(&g_scr.ticket) : "memory");
    epoch >>= 7;
    if (cta < 16 && warp >= 4) {
        const int i = threadIdx.x - 128;
        *reinterpret_cast<uint4*>(out + (i >> 2) * 512 + cta * 32 + (i & 3) * 8) = make_uint4(0, 0, 0, 0);
    }
    const int g8 = lane >> 2, quad = lane & 3;
    const int rh = warp >> 2, g = (warp + 2 * rh) & 3;
    const uint4* const oin = pin(&g_scr.o[((cta >> 4) * 4 + g) * 512 + rh * 64 + lane]);
    uint4* const mine = pin(warp < 4 ? &g_scr.q[cta * 128 + warp * 32 + lane]
                                     : &g_scr.o[(((bh & 7) * 4 + (warp & 2) + (lane >> 4)) * 4 + rank * 2 + (warp & 1)) * 128 +
                                                (bh >> 3) * 16 + (lane & 15)]);
    __nv_bfloat16* const optr = pin(out + (rh * 16 + (g & 1) * 8 + quad * 2 + (g8 & 1)) * 512 + (cta & 15) * 32 + (g >> 1) * 16 + (g8 & 4) + (g8 & 2) * 4);
    bar_sync(0, 288);

    {
        const int kq = warp & 3, mt = warp >> 2;
        float c[4][4];
#pragma unroll
        for (int j = 0; j < 4; j++) c[j][0] = c[j][1] = c[j][2] = c[j][3] = 0.f;
        const int ar = mt * 16 + (lane & 15);
        const uint32_t abase = sb + OFF_X + kq * 8192 + ar * 128;
        const int br = lane & 15;
        const uint32_t bbase = sb + OFF_WQ + (kq * 128 + br) * 64;
        pkt_store(mine, 0, 0, 0, 0, epoch & 1);
        mbar_wait(sb + BAR_W, 0);
#pragma unroll
        for (int ks = 0; ks < 8; ks++) {
            uint32_t a[4], b0[4], b1[4];
            ldsm4(a, abase + (ks >> 2) * 4096 + ((((ks & 3) * 2 + (lane >> 4)) ^ (ar & 7)) << 4));
            ldsm4t(b0, bbase + ks * 1024 + (((lane >> 4) ^ ((br >> 1) & 3)) << 4));
            ldsm4t(b1, bbase + ks * 1024 + (((2 + (lane >> 4)) ^ ((br >> 1) & 3)) << 4));
            mma(c[0], a, b0[0], b0[1]);
            mma(c[1], a, b0[2], b0[3]);
            mma(c[2], a, b1[0], b1[1]);
            mma(c[3], a, b1[2], b1[3]);
        }
        bar_sync(1, 256);
        asm volatile("barrier.cluster.arrive.relaxed.aligned;" ::: "memory");
        const uint32_t rb = sb + OFF_QRED + (kq * 2 + mt) * 2048 + lane * 16;
        sts128f(rb, c[0][0], c[0][1], c[1][0], c[1][1]);
        sts128f(rb + 512, c[2][0], c[2][1], c[3][0], c[3][1]);
        sts128f(rb + 1024, c[0][2], c[0][3], c[1][2], c[1][3]);
        sts128f(rb + 1536, c[2][2], c[2][3], c[3][2], c[3][3]);
        bar_sync(1, 256);
    }
    const uint32_t tag = pin((epoch + 1) & 1);

    if (warp < 4) {
        {
            const uint32_t rb = sb + OFF_QRED + warp * 1024 + lane * 16;
            float4 s0 = lds128f(rb), s1 = lds128f(rb + 512);
#pragma unroll
            for (int kq = 1; kq < 4; kq++) {
                float4 t0 = lds128f(rb + kq * 4096), t1 = lds128f(rb + kq * 4096 + 512);
                s0.x += t0.x; s0.y += t0.y; s0.z += t0.z; s0.w += t0.w;
                s1.x += t1.x; s1.y += t1.y; s1.z += t1.z; s1.w += t1.w;
            }
            pkt_store(mine, pack_bf16_tagged(s0.x, s0.y, tag), pack_bf16(s0.z, s0.w),
                      pack_bf16_tagged(s1.x, s1.y, tag), pack_bf16(s1.z, s1.w), tag);
            __syncwarp();
            if (lane < NST - NST0) mbar_arrive(sb + BAR_EMPTY + 8 * (NST0 + lane));
        }
        __nanosleep(Q_DELAY_NS);
        uint32_t q[8][4];
        {
            Pkt v[8];
            const uint4* qp = &g_scr.q[(((bh & 7) * 4 + (lane >> 4)) * 4) * 128 + (bh >> 3) * 16 + (lane & 15)];
            pkt_issue<8, 4, 128, 1024>(v, qp);
            pkt_poll<8, 4, 128, 1024>(v, qp, tag);
#pragma unroll
            for (int dq = 0; dq < 4; dq++) {
                const Pkt &a = v[dq], &b = v[4 + dq];
                q[2 * dq][0] = a.w0();     q[2 * dq][1] = b.w0();     q[2 * dq][2] = a.w1();     q[2 * dq][3] = b.w1();
                q[2 * dq + 1][0] = a.w2(); q[2 * dq + 1][1] = b.w2(); q[2 * dq + 1][2] = a.w3(); q[2 * dq + 1][3] = b.w3();
            }
        }
        asm volatile("barrier.cluster.wait.acquire.aligned;" ::: "memory");
        constexpr float C = 0.08838834764831845f * 1.4426950408889634f;
        float mc0 = -INFINITY, mc1 = -INFINITY, l0 = 0.f, l1 = 0.f;
        const int key = warp * 16 + (lane >> 4) * 8 + (lane & 7);
        const uint32_t koff = key * 128;
        const int ksel = (lane >> 3) & 1, kx = lane & 7;
        const uint32_t rp = mapa(sb + OFF_P + NP * 2048 + warp * 512 + lane * 16, rank ^ 1);
        const uint32_t ra = mapa(sb + OFF_ALPHA + NP * 64 + g8 * 4, rank ^ 1), rfull = mapa(sb + BAR_PFULL + 8 * NP, rank ^ 1);
        int st = 0;
        uint32_t par = 0;
#pragma unroll 1
        for (int i = 0; i < NT; i++) {
            const uint32_t kb = sb + st * STAGE + koff;
            float s[2][2][4];
#pragma unroll
            for (int j = 0; j < 4; j++) s[0][0][j] = s[0][1][j] = s[1][0][j] = s[1][1][j] = 0.f;
            mbar_wait(sb + BAR_FULL + 8 * st, par);
#pragma unroll
            for (int ks = 0; ks < 8; ks++) {
                uint32_t b[4];
                ldsm4(b, kb + (ks >> 2) * 8192 + ((((ks & 3) * 2 + ksel) ^ kx) << 4));
                mma(s[ks & 1][0], q[ks], b[0], b[1]);
                mma(s[ks & 1][1], q[ks], b[2], b[3]);
            }
            __syncwarp();
            if (lane == 0) mbar_arrive(sb + BAR_EMPTY + 8 * st);
            st += i < KA ? 1 : 2;
            if (st >= NST) { st -= NST; par ^= 1; }
            float sv[2][4];
#pragma unroll
            for (int j = 0; j < 4; j++) { sv[0][j] = s[0][0][j] + s[1][0][j]; sv[1][j] = s[0][1][j] + s[1][1][j]; }
            float t0 = fmaxf(fmaxf(sv[0][0], sv[0][1]), fmaxf(sv[1][0], sv[1][1]));
            float t1 = fmaxf(fmaxf(sv[0][2], sv[0][3]), fmaxf(sv[1][2], sv[1][3]));
            t0 = fmaxf(t0, __shfl_xor_sync(0xffffffffu, t0, 1));
            t1 = fmaxf(t1, __shfl_xor_sync(0xffffffffu, t1, 1));
            t0 = fmaxf(t0, __shfl_xor_sync(0xffffffffu, t0, 2));
            t1 = fmaxf(t1, __shfl_xor_sync(0xffffffffu, t1, 2));
            const uint32_t wm = sb + OFF_WMAX + (i & 1) * 256 + g8 * 16;
            if (quad == 0) { sts32f(wm + warp * 4, t0); sts32f(wm + 128 + warp * 4, t1); }
            bar_sync(2, 128);
            const float4 w0 = lds128f(wm), w1 = lds128f(wm + 128);
            const float n0 = fmaxf(mc0, fmaxf(fmaxf(w0.x, w0.y), fmaxf(w0.z, w0.w)) * C);
            const float n1 = fmaxf(mc1, fmaxf(fmaxf(w1.x, w1.y), fmaxf(w1.z, w1.w)) * C);
            const float a0 = ex2(mc0 - n0), a1 = ex2(mc1 - n1);
            mc0 = n0; mc1 = n1;
            float p[2][4];
#pragma unroll
            for (int j = 0; j < 2; j++) {
                p[j][0] = ex2(fmaf(sv[j][0], C, -n0)); p[j][1] = ex2(fmaf(sv[j][1], C, -n0));
                p[j][2] = ex2(fmaf(sv[j][2], C, -n1)); p[j][3] = ex2(fmaf(sv[j][3], C, -n1));
            }
            l0 = l0 * a0 + ((p[0][0] + p[0][1]) + (p[1][0] + p[1][1]));
            l1 = l1 * a1 + ((p[0][2] + p[0][3]) + (p[1][2] + p[1][3]));
            const int slot = i % NP;
            if (i >= NP) {
                mbar_wait(sb + BAR_PEMPTY + 8 * slot, (i / NP - 1) & 1);
                mbar_wait(sb + BAR_PEMPTY + 8 * (NP + slot), (i / NP - 1) & 1);
            }
            const uint32_t p0 = pack_bf16(p[0][0], p[0][1]), p1 = pack_bf16(p[0][2], p[0][3]), p2 = pack_bf16(p[1][0], p[1][1]),
                           p3 = pack_bf16(p[1][2], p[1][3]);
            asm volatile("st.async.weak.shared::cluster.mbarrier::complete_tx::bytes.v4.b32 [%0], {%1,%2,%3,%4}, [%5];"
                         ::"r"(rp + slot * 2048), "r"(p1), "r"(p0), "r"(p3), "r"(p2), "r"(rfull + 8 * slot) : "memory");
            sts128(sb + OFF_P + slot * 2048 + warp * 512 + lane * 16, p0, p1, p2, p3);
            if (warp == 0 && quad == 0) {
                asm volatile("st.async.weak.shared::cluster.mbarrier::complete_tx::bytes.f32 [%0], %1, [%2];"
                             ::"r"(ra + slot * 64), "f"(a1), "r"(rfull + 8 * slot) : "memory");
                asm volatile("st.async.weak.shared::cluster.mbarrier::complete_tx::bytes.f32 [%0], %1, [%2];"
                             ::"r"(ra + slot * 64 + 32), "f"(a0), "r"(rfull + 8 * slot) : "memory");
                sts32f(sb + OFF_ALPHA + slot * 64 + g8 * 4, a0);
                sts32f(sb + OFF_ALPHA + slot * 64 + 32 + g8 * 4, a1);
            }
            __syncwarp();
            if (lane == 0) mbar_arrive(sb + BAR_PFULL + 8 * slot);
        }
        l0 += __shfl_xor_sync(0xffffffffu, l0, 1);
        l1 += __shfl_xor_sync(0xffffffffu, l1, 1);
        l0 += __shfl_xor_sync(0xffffffffu, l0, 2);
        l1 += __shfl_xor_sync(0xffffffffu, l1, 2);
        if (quad == 0) {
            sts32f(sb + OFF_LSUM + g8 * 16 + warp * 4, l0);
            sts32f(sb + OFF_LSUM + 128 + g8 * 16 + warp * 4, l1);
            if (warp == 0) { sts32f(sb + OFF_MROW + g8 * 4, mc0); sts32f(sb + OFF_MROW + 32 + g8 * 4, mc1); }
        }
        bar_sync(2, 128);
        if (warp == 0) {
            if (lane < 16) {
                const float4 lv = lds128f(sb + OFF_LSUM + lane * 16);
                const float l = (lv.x + lv.y) + (lv.z + lv.w), m = lds32f(sb + OFF_MROW + lane * 4);
                asm volatile("st.async.weak.shared::cluster.mbarrier::complete_tx::bytes.v2.f32 [%0], {%1,%2}, [%3];"
                             ::"r"(mapa(sb + OFF_STAT + lane * 8, rank ^ 1)), "f"(m), "f"(l), "r"(mapa(sb + BAR_STAT, rank ^ 1)) : "memory");
                mbar_wait(sb + BAR_STAT, 0);
                const float pm = lds32f(sb + OFF_STAT + lane * 8), pl = lds32f(sb + OFF_STAT + lane * 8 + 4);
                const float mm = fmaxf(m, pm);
                const float e = ex2(m - mm), pe = ex2(pm - mm);
                const float inv = __fdividef(1.f, rank ? pl * pe + l * e : l * e + pl * pe);
                sts32f(sb + OFF_F + lane * 4, e * inv);
                sts32f(sb + OFF_F + 64 + (lane ^ 8) * 4, pe * inv);
            }
            __syncwarp();
            if (lane == 0) mbar_arrive(sb + BAR_F);
        }
        mbar_wait(sb + BAR_D, 0);
    } else {
        const int w = warp - 4;
        asm volatile("barrier.cluster.wait.acquire.aligned;" ::: "memory");
        if (threadIdx.x == 128) {
            asm volatile("red.relaxed.gpu.global.add.u32 [%0], 1;" ::"l"(&g_scr.ticket) : "memory");
            if (cta < 16) asm volatile("st.release.gpu.global.u32 [%0], %1;" ::"l"(&g_scr.zeroed[cta * 32]), "r"(epoch + 1) : "memory");
            unsigned z;
#pragma unroll 1
            for (int it = 0;; it++) {
                asm volatile("ld.acquire.gpu.global.u32 %0, [%1];" : "=r"(z) : "l"(&g_scr.zeroed[(cta & 15) * 32]) : "memory");
                if (z == epoch + 1) break;
                if (it > (1 << 20)) __trap();
                __nanosleep(200);
            }
        }
        __syncwarp();
        const int src = w >> 1, ds = w & 1;
        const uint32_t pbase = pin(sb + OFF_P + src * NP * 2048 + lane * 16), abase = pin(sb + OFF_ALPHA + src * NP * 64 + g8 * 4);
        const uint32_t pfull = pin(sb + BAR_PFULL + src * NP * 8);
        const uint32_t pempty = src ? mapa(sb + BAR_PEMPTY + 8 * NP, rank ^ 1) : mapa(sb + BAR_PEMPTY, rank);
        float o[4][4], t[2][4][4];
#pragma unroll
        for (int j = 0; j < 16; j++) (&o[0][0])[j] = (&t[0][0][0])[j] = (&t[1][0][0])[j] = 0.f;
        const uint32_t voff = ((rank ^ src) * 64 + (lane & 15)) * 128;
        const int vc = ds * 4 + (lane >> 4), vx = lane & 7;
        const uint32_t v0 = pin(sb + voff + ((vc ^ vx) << 4)), v1 = pin(sb + voff + (((vc + 2) ^ vx) << 4));
        uint32_t p[4][4], b0[4][4], b1[4][4];
        float a0 = 0.f, a1 = 0.f;
        auto load_v = [&](int st) {
#pragma unroll
            for (int j = 0; j < 4; j++) {
                ldsm4t(b0[j], v0 + st * STAGE + j * 2048);
                ldsm4t(b1[j], v1 + st * STAGE + j * 2048);
            }
        };
        auto next_p = [&](int i) {
            const int slot = i % NP;
            mbar_wait(pfull + 8 * slot, (i / NP) & 1);
#pragma unroll
            for (int j = 0; j < 4; j++) lds128(p[j], pbase + slot * 2048 + j * 512);
            const float n0 = lds32f(abase + slot * 64), n1 = lds32f(abase + slot * 64 + 32);
            __syncwarp();
            if (lane == 0 && i < NT - NP) {
                if (w == 2) mbar_expect_tx(pfull + 8 * slot, 2048 + 64);
                asm volatile("mbarrier.arrive.relaxed.cluster.shared::cluster.b64 _, [%0];"
                             ::"r"(pempty + 8 * slot + ((p[3][3] | __float_as_uint(n1)) & zero)) : "memory");
            }
#pragma unroll
            for (int j = 0; j < 4; j++) {
                o[j][0] = fmaf(o[j][0], a0, t[0][j][0] + t[1][j][0]); o[j][1] = fmaf(o[j][1], a0, t[0][j][1] + t[1][j][1]);
                o[j][2] = fmaf(o[j][2], a1, t[0][j][2] + t[1][j][2]); o[j][3] = fmaf(o[j][3], a1, t[0][j][3] + t[1][j][3]);
            }
            a0 = n0; a1 = n1;
        };
        auto pv = [&]() {
#pragma unroll
            for (int j = 0; j < 16; j++) (&t[0][0][0])[j] = (&t[1][0][0])[j] = 0.f;
#pragma unroll
            for (int j = 0; j < 4; j++) {
                mma(t[j & 1][0], p[j], b0[j][0], b0[j][1]);
                mma(t[j & 1][1], p[j], b0[j][2], b0[j][3]);
                mma(t[j & 1][2], p[j], b1[j][0], b1[j][1]);
                mma(t[j & 1][3], p[j], b1[j][2], b1[j][3]);
            }
        };
        int st = KA + 1;
        uint32_t par = 0;
#pragma unroll 1
        for (int i = 0; i < NT - 1; i++) {
            mbar_wait(sb + BAR_FULL + 8 * st, par);
            load_v(st);
            next_p(i);
            pv();
            __syncwarp();
            if (lane == 0) mbar_arrive(sb + BAR_EMPTY + 8 * st);
            st += i < NT - KA - 1 ? 2 : 1;
            if (st >= NST) { st -= NST; par ^= 1; }
        }
        constexpr int LST = (2 * NT - 1) % NST, LPAR = ((2 * NT - 1) / NST) & 1;
        const bool landed = mbar_test(sb + BAR_FULL + 8 * LST, LPAR);
        if (landed) load_v(LST);
        next_p(NT - 1);
        mbar_wait(sb + BAR_F, 0);
        const float f0 = lds32f(sb + OFF_F + src * 64 + g8 * 4), f1 = lds32f(sb + OFF_F + src * 64 + 32 + g8 * 4);
        a0 *= f0; a1 *= f1;
#pragma unroll
        for (int j = 0; j < 4; j++) {
            o[j][0] *= a0; o[j][1] *= a0; o[j][2] *= a1; o[j][3] *= a1;
            asm volatile("" : "+f"(o[j][0]), "+f"(o[j][1]), "+f"(o[j][2]), "+f"(o[j][3]));
        }
        if (!landed) {
            mbar_wait(sb + BAR_FULL + 8 * LST, LPAR);
            load_v(LST);
        }
        pv();
#pragma unroll
        for (int j = 0; j < 4; j++) {
            o[j][0] = fmaf(t[0][j][0] + t[1][j][0], f0, o[j][0]); o[j][1] = fmaf(t[0][j][1] + t[1][j][1], f0, o[j][1]);
            o[j][2] = fmaf(t[0][j][2] + t[1][j][2], f1, o[j][2]); o[j][3] = fmaf(t[0][j][3] + t[1][j][3], f1, o[j][3]);
        }
        {
            const uint32_t ours = sb + OFF_MERGE + w * 1024 + lane * 16, theirs = sb + OFF_MERGE + (w ^ 2) * 1024 + lane * 16;
            sts128f(theirs, o[0][2], o[0][3], o[1][2], o[1][3]);
            sts128f(theirs + 512, o[2][2], o[2][3], o[3][2], o[3][3]);
            bar_sync(5 + ds, 64);
            const float4 r0 = lds128f(ours), r1 = lds128f(ours + 512);
            pkt_store(mine, pack_bf16(o[0][0] + r0.x, o[0][1] + r0.y), pack_bf16(o[1][0] + r0.z, o[1][1] + r0.w),
                      pack_bf16(o[2][0] + r1.x, o[2][1] + r1.y), pack_bf16(o[3][0] + r1.z, o[3][1] + r1.w), tag);
        }
        if (lane == 0) mbar_arrive(sb + BAR_D);
    }

    {
        uint32_t a[8][2][4];
        const int kr = (lane >> 4) * 8 + (lane & 7);
        const int wc = (lane >> 3) & 1, wx = (kr >> 1) & 3;
        const uint32_t wb0 = pin(sb + OFF_WO + (g * 128 + kr) * 64 + ((wc ^ wx) << 4));
        const uint32_t wb1 = pin(sb + OFF_WO + (g * 128 + kr) * 64 + (((wc + 2) ^ wx) << 4));
        const uint32_t red = pin(sb + OFF_PRED + rh * 8192 + lane * 16);
        const uint32_t rw = pin(red + g * 512), rr = pin(red + (g & 1) * 4096 + (g >> 1) * 2048);
        const uint32_t wobar = sb + BAR_WO + 8 * g;
        constexpr uint32_t wopar = 0;
        auto wo_within = [&](uint32_t clks) {
            uint32_t c0, c1;
            bool in;
            asm volatile("mov.u32 %0, %%clock;" : "=r"(c0));
            do {
                in = mbar_test(wobar, wopar);
                asm volatile("mov.u32 %0, %%clock;" : "=r"(c1));
            } while (!in && c1 - c0 < clks);
            return in;
        };
        Pkt v[8];
        const bool in0 = wo_within(O_DELAY);
        pkt_issue<8, 4, 128, 32>(v, oin);
        if (!in0) {
#pragma unroll 1
            for (int it = 0; !wo_within(O_PERIOD); it++) {
                uint32_t b[8];
#pragma unroll
                for (int i = 0; i < 8; i++) b[i] = v[i].bad(tag);
                if (it > (1 << 16)) __trap();
#pragma unroll
                for (int i = 0; i < 8; i++) pkt_reload(v[i], oin + (i >> 2) * 32 + (i & 3) * 128, b[i]);
            }
        }
#pragma unroll
        for (int ks = 0; ks < 8; ks++) {
            ldsm4t(a[ks][0], wb0 + ks * 1024);
            ldsm4t(a[ks][1], wb1 + ks * 1024);
        }
        pkt_poll<8, 4, 128, 32>(v, oin, tag | (a[7][1][3] & zero));
        float c[2][2][2][4];
#pragma unroll
        for (int j = 0; j < 32; j++) (&c[0][0][0][0])[j] = 0.f;
#pragma unroll
        for (int dq = 0; dq < 4; dq++)
#pragma unroll
            for (int t = 0; t < 2; t++) {
                mma(c[t][0][0], a[2 * dq][0], v[t * 4 + dq].w0(), v[t * 4 + dq].w1());
                mma(c[t][1][0], a[2 * dq][1], v[t * 4 + dq].w0(), v[t * 4 + dq].w1());
                mma(c[t][0][1], a[2 * dq + 1][0], v[t * 4 + dq].w2(), v[t * 4 + dq].w3());
                mma(c[t][1][1], a[2 * dq + 1][1], v[t * 4 + dq].w2(), v[t * 4 + dq].w3());
            }
#pragma unroll
        for (int t = 0; t < 2; t++)
#pragma unroll
            for (int mt = 0; mt < 2; mt++)
                sts128f(rw + t * 4096 + mt * 2048, c[t][mt][0][0] + c[t][mt][1][0], c[t][mt][0][1] + c[t][mt][1][1],
                        c[t][mt][0][2] + c[t][mt][1][2], c[t][mt][0][3] + c[t][mt][1][3]);
        bar_sync(3 + rh, 128);
        const float4 s0 = lds128f(rr), s1 = lds128f(rr + 512), s2 = lds128f(rr + 1024), s3 = lds128f(rr + 1536);
        const uint32_t r0 = pack_bf16((s0.x + s1.x) + (s2.x + s3.x), (s0.z + s1.z) + (s2.z + s3.z));
        const uint32_t r1 = pack_bf16((s0.y + s1.y) + (s2.y + s3.y), (s0.w + s1.w) + (s2.w + s3.w));
        const bool odd = g8 & 1;
        const uint32_t got = __shfl_xor_sync(0xffffffffu, odd ? r0 : r1, 4);
        const uint32_t lo = odd ? got : r0, hi = odd ? r1 : got;
        const uint32_t w0 = __byte_perm(lo, hi, 0x5410), w1 = __byte_perm(lo, hi, 0x7632);
        const bool up = g8 & 2;
        const uint32_t got2 = __shfl_xor_sync(0xffffffffu, up ? w0 : w1, 8);
        asm volatile("red.relaxed.gpu.global.add.noftz.v2.bf16x2 [%0], {%1, %2};" ::"l"(optr), "r"(up ? got2 : w0), "r"(up ? w1 : got2) : "memory");
    }

}

__global__ void fb_proj(const __nv_bfloat16* a_bf, const float* a_f, const __nv_bfloat16* w, int K, int N, float* o_f,
                        __nv_bfloat16* o_bf) {
    const int c = blockIdx.x * blockDim.x + threadIdx.x, r = blockIdx.y;
    float s = 0.f;
    for (int k = 0; k < K; k++) s += (a_bf ? __bfloat162float(a_bf[r * K + k]) : a_f[r * K + k]) * __bfloat162float(w[k * N + c]);
    if (o_bf) o_bf[r * N + c] = __float2bfloat16(s);
    else o_f[r * N + c] = __bfloat162float(__float2bfloat16(s));
}
__global__ void fb_attn(const __nv_bfloat16* kc, const __nv_bfloat16* vc) {
    __shared__ float sc[2048], red[128];
    const int r = blockIdx.x, hq = blockIdx.y, t = threadIdx.x;
    const size_t base = (size_t)((r >> 2) * 8 + (hq >> 2)) * 2048 * 128;
    float m = -INFINITY, l = 0.f, acc = 0.f;
    for (int j = t; j < 2048; j += 128) {
        float s = 0.f;
        for (int d = 0; d < 128; d++) s += g_scr.fq[r * 4096 + hq * 128 + d] * __bfloat162float(kc[base + j * 128 + d]);
        sc[j] = s * 0.08838834764831845f;
        m = fmaxf(m, sc[j]);
    }
    red[t] = m;
    __syncthreads();
    for (int i = 0; i < 128; i++) m = fmaxf(m, red[i]);
    for (int j = t; j < 2048; j += 128) sc[j] = __expf(sc[j] - m);
    __syncthreads();
    for (int j = 0; j < 2048; j++) {
        l += sc[j];
        acc += sc[j] * __bfloat162float(vc[base + j * 128 + t]);
    }
    g_scr.fo[r * 4096 + hq * 128 + t] = __bfloat162float(__float2bfloat16(acc / l));
}

typedef CUresult (*EncodeFn)(CUtensorMap*, CUtensorMapDataType, cuuint32_t, void*, const cuuint64_t*, const cuuint64_t*,
                             const cuuint32_t*, const cuuint32_t*, CUtensorMapInterleave, CUtensorMapSwizzle,
                             CUtensorMapL2promotion, CUtensorMapFloatOOBfill);

static void encode(EncodeFn fn, CUtensorMap* m, void* p, int rank, const cuuint64_t* dims, const cuuint64_t* strides,
                   const cuuint32_t* box, CUtensorMapSwizzle sw) {
    const cuuint32_t es[3] = {1, 1, 1};
    fn(m, CU_TENSOR_MAP_DATA_TYPE_BFLOAT16, rank, p, dims, strides, box, es, CU_TENSOR_MAP_INTERLEAVE_NONE, sw,
       CU_TENSOR_MAP_L2_PROMOTION_L2_256B, CU_TENSOR_MAP_FLOAT_OOB_FILL_NONE);
}

}

extern "C" void kernel_launch(void* const* d_in, const int* in_sizes, int n_in, void* d_out, int out_size) {
    using namespace gqa;
    static EncodeFn fn = nullptr;
    static uint32_t slot_ns = SLOT_NS;
    static bool fits = false;
    if (!fn) {
        int dev = 0, khz = 0, bits = 0;
        cudaGetDevice(&dev);
        cudaDeviceGetAttribute(&khz, cudaDevAttrMemoryClockRate, dev);
        cudaDeviceGetAttribute(&bits, cudaDevAttrGlobalMemoryBusWidth, dev);
        if (khz > 0 && bits > 0) slot_ns = (uint32_t)((double)NCTA * STAGE / (0.955 * 2.0 * khz * 1e-6 * (bits / 8)));
        void* p = nullptr;
        cudaDriverEntryPointQueryResult qr;
        cudaGetDriverEntryPoint("cuTensorMapEncodeTiled", &p, cudaEnableDefault, &qr);
        fn = (EncodeFn)p;
        cudaFuncSetAttribute(gqa_kernel, cudaFuncAttributeMaxDynamicSharedMemorySize, SMEM_BYTES);
        cudaLaunchConfig_t cfg = {};
        cfg.gridDim = dim3(NCTA);
        cfg.blockDim = dim3(288);
        cfg.dynamicSmemBytes = SMEM_BYTES;
        int clusters = 0;
        fits = cudaOccupancyMaxActiveClusters(&clusters, gqa_kernel, &cfg) == cudaSuccess && clusters >= NCTA / 2;
    }
    if (!fits) {
        Scratch* scr = nullptr;
        cudaGetSymbolAddress((void**)&scr, g_scr);
        float *fq = scr->fq, *fo = scr->fo;
        fb_proj<<<dim3(16, 32), 256, 0, cudaStreamPerThread>>>((const __nv_bfloat16*)d_in[0], nullptr, (const __nv_bfloat16*)d_in[3], 512,
                                                               4096, fq, nullptr);
        fb_attn<<<dim3(32, 32), 128, 0, cudaStreamPerThread>>>((const __nv_bfloat16*)d_in[1], (const __nv_bfloat16*)d_in[2]);
        fb_proj<<<dim3(2, 32), 256, 0, cudaStreamPerThread>>>(nullptr, fo, (const __nv_bfloat16*)d_in[4], 4096, 512, nullptr,
                                                              (__nv_bfloat16*)d_out);
        return;
    }
    CUtensorMap tmK, tmV, tmX, tmWq, tmWo;
    {
        const cuuint64_t dims[3] = {64, 8 * 8 * 2048, 2}, str[2] = {256, 128};
        const cuuint32_t box[3] = {64, 64, 2};
        encode(fn, &tmK, d_in[1], 3, dims, str, box, CU_TENSOR_MAP_SWIZZLE_128B);
        const cuuint64_t dv[2] = {128, 8 * 8 * 2048}, sv[1] = {256};
        const cuuint32_t bv[2] = {64, 128};
        encode(fn, &tmV, d_in[2], 2, dv, sv, bv, CU_TENSOR_MAP_SWIZZLE_128B);
    }
    {
        const cuuint64_t dims[3] = {64, 32, 8}, str[2] = {1024, 128};
        const cuuint32_t box[3] = {64, 32, 8};
        encode(fn, &tmX, d_in[0], 3, dims, str, box, CU_TENSOR_MAP_SWIZZLE_128B);
    }
    {
        const cuuint64_t dq[2] = {4096, 512}, sq[1] = {8192}, dw[2] = {512, 4096}, sw[1] = {1024};
        const cuuint32_t box[2] = {32, 256};
        encode(fn, &tmWq, d_in[3], 2, dq, sq, box, CU_TENSOR_MAP_SWIZZLE_64B);
        const cuuint32_t boxo[2] = {32, 128};
        encode(fn, &tmWo, d_in[4], 2, dw, sw, boxo, CU_TENSOR_MAP_SWIZZLE_64B);
    }
    gqa_kernel<<<NCTA, 288, SMEM_BYTES, cudaStreamPerThread>>>(Ptrs{{(const uint8_t*)d_in[3], nullptr}}, (__nv_bfloat16*)d_out, slot_ns, 0u, tmK, tmV, tmX,
                                                               tmWq, tmWo);
}
```

```cpp
#include <cuda_runtime.h>
#include <cuda_bf16.h>
#include <cuda.h>
#include <stdint.h>

namespace gqa {

constexpr int PA_NS = 2780;
constexpr int SLOT_NS = 655;
constexpr int WO_SLOT = 2880;
constexpr int WO_STEP = 65;
constexpr int Q_DELAY_NS = 1000;
constexpr int O_DELAY = 1000;
constexpr int O_PERIOD = 350;
constexpr int PF_BYTES = 8192;

constexpr int NCTA = 128;
constexpr int NT = 16;
constexpr int NST = 13;
constexpr int NST0 = 10;
constexpr int WIN0 = 3;
constexpr int WIN = 8;
constexpr int WSW = 8;
constexpr int KA = 2;
constexpr int NP = 4;
constexpr int STAGE = 16384;

constexpr int OFF_WQ = NST0 * STAGE;
constexpr int OFF_X = OFF_WQ + 32768;
constexpr int OFF_QRED = OFF_X;
constexpr int OFF_WO = ((2 * NT) % NST) * STAGE;
constexpr int OFF_P = NST * STAGE;
constexpr int OFF_MERGE = (((2 * NT) % NST) + 3) * STAGE;
constexpr int OFF_ALPHA = (NST + 1) * STAGE + 512;
constexpr int OFF_WMAX = OFF_ALPHA + 2 * NP * 64;
constexpr int OFF_LSUM = OFF_WMAX + 512;
constexpr int OFF_MROW = OFF_LSUM + 256;
constexpr int OFF_STAT = OFF_MROW + 64;
constexpr int OFF_F = OFF_STAT + 128;
constexpr int OFF_PRED = (((2 * NT) % NST) + 2) * STAGE;
constexpr int OFF_BAR = (NST + 1) * STAGE;
constexpr int BAR_FULL = OFF_BAR;
constexpr int BAR_EMPTY = BAR_FULL + 8 * NST;
constexpr int BAR_PFULL = BAR_EMPTY + 8 * NST;
constexpr int BAR_PEMPTY = BAR_PFULL + 16 * NP;
constexpr int BAR_W = BAR_PEMPTY + 16 * NP;
constexpr int BAR_STAT = BAR_W + 8;
constexpr int BAR_F = BAR_STAT + 8;
constexpr int BAR_D = BAR_F + 8;
constexpr int BAR_WO = BAR_D + 8;
constexpr int SMEM_BYTES = OFF_F + 128;
static_assert(2 * NP * 2048 <= STAGE, "P slots overflow");
static_assert(BAR_WO + 32 <= OFF_ALPHA, "barriers overflow");
static_assert((2 * NT) % NST + 3 < NST, "wo / partial slots must not wrap");
static_assert(SMEM_BYTES <= 232448, "too much shared memory");

struct __align__(1024) Scratch {
    uint4 q[32 * 4 * 8 * 16];
    uint4 o[32 * 4 * 8 * 16];
    unsigned ticket;
    unsigned pad[31];
    unsigned zeroed[16 * 32];
    float fq[32 * 4096], fo[32 * 4096];
};
__device__ Scratch g_scr;

__device__ __forceinline__ void mbar_init(uint32_t bar, uint32_t cnt) {
    asm volatile("mbarrier.init.shared::cta.b64 [%0], %1;" ::"r"(bar), "r"(cnt) : "memory");
}
__device__ __forceinline__ void mbar_expect_tx(uint32_t bar, uint32_t bytes) {
    asm volatile("mbarrier.arrive.expect_tx.shared::cta.b64 _, [%0], %1;" ::"r"(bar), "r"(bytes) : "memory");
}
__device__ __forceinline__ void mbar_arrive(uint32_t bar) {
    asm volatile("mbarrier.arrive.shared::cta.b64 _, [%0];" ::"r"(bar) : "memory");
}
__device__ __forceinline__ bool mbar_try(uint32_t bar, uint32_t parity) {
    uint32_t ok;
    asm volatile("{\n.reg .pred p;\nmbarrier.try_wait.parity.shared::cta.b64 p, [%1], %2;\nselp.u32 %0, 1, 0, p;\n}"
                 : "=r"(ok) : "r"(bar), "r"(parity) : "memory");
    return ok;
}
__device__ __forceinline__ bool mbar_test(uint32_t bar, uint32_t parity) {
    uint32_t ok;
    asm volatile("{\n.reg .pred p;\nmbarrier.test_wait.parity.shared::cta.b64 p, [%1], %2;\nselp.u32 %0, 1, 0, p;\n}"
                 : "=r"(ok) : "r"(bar), "r"(parity) : "memory");
    return ok;
}
__device__ __forceinline__ void mbar_wait(uint32_t bar, uint32_t parity) {
#pragma unroll 1
    for (int i = 0; !mbar_try(bar, parity); i++)
        if (i > (1 << 20)) __trap();
}
__device__ __forceinline__ void tma2d(uint32_t dst, const CUtensorMap* m, int c0, int c1, uint32_t bar) {
    asm volatile("cp.async.bulk.tensor.2d.shared::cluster.global.mbarrier::complete_tx::bytes [%0], [%1, {%3, %4}], [%2];"
                 ::"r"(dst), "l"(m), "r"(bar), "r"(c0), "r"(c1) : "memory");
}
__device__ __forceinline__ void tma3d(uint32_t dst, const CUtensorMap* m, int c0, int c1, int c2, uint32_t bar) {
    asm volatile("cp.async.bulk.tensor.3d.shared::cluster.global.mbarrier::complete_tx::bytes [%0], [%1, {%3, %4, %5}], [%2];"
                 ::"r"(dst), "l"(m), "r"(bar), "r"(c0), "r"(c1), "r"(c2) : "memory");
}
__device__ __forceinline__ void tma2d_hint(uint32_t dst, const CUtensorMap* m, int c0, int c1, uint32_t bar, uint64_t pol) {
    asm volatile("cp.async.bulk.tensor.2d.shared::cluster.global.mbarrier::complete_tx::bytes.L2::cache_hint [%0], [%1, {%3, %4}], [%2], %5;"
                 ::"r"(dst), "l"(m), "r"(bar), "r"(c0), "r"(c1), "l"(pol) : "memory");
}
__device__ __forceinline__ uint32_t mapa(uint32_t addr, uint32_t cta_rank) {
    uint32_t r;
    asm("mapa.shared::cluster.u32 %0, %1, %2;" : "=r"(r) : "r"(addr), "r"(cta_rank));
    return r;
}
__device__ __forceinline__ void tma3d_hint(uint32_t dst, const CUtensorMap* m, int c0, int c1, int c2, uint32_t bar, uint64_t pol) {
    asm volatile("cp.async.bulk.tensor.3d.shared::cluster.global.mbarrier::complete_tx::bytes.L2::cache_hint [%0], [%1, {%3, %4, %5}], [%2], %6;"
                 ::"r"(dst), "l"(m), "r"(bar), "r"(c0), "r"(c1), "r"(c2), "l"(pol) : "memory");
}
__device__ __forceinline__ void ldsm4(uint32_t (&r)[4], uint32_t addr) {
    asm volatile("ldmatrix.sync.aligned.m8n8.x4.shared.b16 {%0,%1,%2,%3}, [%4];"
                 : "=r"(r[0]), "=r"(r[1]), "=r"(r[2]), "=r"(r[3]) : "r"(addr) : "memory");
}
__device__ __forceinline__ void ldsm4t(uint32_t (&r)[4], uint32_t addr) {
    asm volatile("ldmatrix.sync.aligned.m8n8.x4.trans.shared.b16 {%0,%1,%2,%3}, [%4];"
                 : "=r"(r[0]), "=r"(r[1]), "=r"(r[2]), "=r"(r[3]) : "r"(addr) : "memory");
}
__device__ __forceinline__ void mma(float (&c)[4], const uint32_t (&a)[4], uint32_t b0, uint32_t b1) {
    asm volatile("mma.sync.aligned.m16n8k16.row.col.f32.bf16.bf16.f32 {%0,%1,%2,%3}, {%4,%5,%6,%7}, {%8,%9}, {%0,%1,%2,%3};"
                 : "+f"(c[0]), "+f"(c[1]), "+f"(c[2]), "+f"(c[3])
                 : "r"(a[0]), "r"(a[1]), "r"(a[2]), "r"(a[3]), "r"(b0), "r"(b1));
}
__device__ __forceinline__ uint32_t pack_bf16(float lo, float hi) {
    uint32_t r;
    asm("cvt.rn.bf16x2.f32 %0, %1, %2;" : "=r"(r) : "f"(hi), "f"(lo));
    return r;
}
__device__ __forceinline__ float ex2(float x) {
    float y;
    asm("ex2.approx.ftz.f32 %0, %1;" : "=f"(y) : "f"(x));
    return y;
}
__device__ __forceinline__ void sts128(uint32_t addr, uint32_t a, uint32_t b, uint32_t c, uint32_t d) {
    asm volatile("st.shared.v4.b32 [%0], {%1,%2,%3,%4};" ::"r"(addr), "r"(a), "r"(b), "r"(c), "r"(d) : "memory");
}
__device__ __forceinline__ void sts128f(uint32_t addr, float a, float b, float c, float d) {
    asm volatile("st.shared.v4.f32 [%0], {%1,%2,%3,%4};" ::"r"(addr), "f"(a), "f"(b), "f"(c), "f"(d) : "memory");
}
__device__ __forceinline__ void sts32f(uint32_t addr, float a) {
    asm volatile("st.shared.f32 [%0], %1;" ::"r"(addr), "f"(a) : "memory");
}
__device__ __forceinline__ void lds128(uint32_t (&r)[4], uint32_t addr) {
    asm volatile("ld.shared.v4.b32 {%0,%1,%2,%3}, [%4];" : "=r"(r[0]), "=r"(r[1]), "=r"(r[2]), "=r"(r[3]) : "r"(addr) : "memory");
}
__device__ __forceinline__ float4 lds128f(uint32_t addr) {
    float4 v;
    asm volatile("ld.shared.v4.f32 {%0,%1,%2,%3}, [%4];" : "=f"(v.x), "=f"(v.y), "=f"(v.z), "=f"(v.w) : "r"(addr) : "memory");
    return v;
}
__device__ __forceinline__ float lds32f(uint32_t addr) {
    float v;
    asm volatile("ld.shared.f32 %0, [%1];" : "=f"(v) : "r"(addr) : "memory");
    return v;
}
__device__ __forceinline__ void bar_sync(int id, int n) { asm volatile("bar.sync %0, %1;" ::"r"(id), "r"(n) : "memory"); }
template <typename T> __device__ __forceinline__ T* pin(T* p) { asm volatile("" : "+l"(p)); return p; }
__device__ __forceinline__ uint32_t pin(uint32_t v) { asm volatile("" : "+r"(v)); return v; }

struct Pkt {
    uint64_t lo, hi;
    __device__ __forceinline__ uint32_t w0() const { return (uint32_t)lo; }
    __device__ __forceinline__ uint32_t w1() const { return (uint32_t)(lo >> 32); }
    __device__ __forceinline__ uint32_t w2() const { return (uint32_t)hi; }
    __device__ __forceinline__ uint32_t w3() const { return (uint32_t)(hi >> 32); }
    __device__ __forceinline__ uint32_t bad(uint32_t tag) const {
        uint32_t r;
        asm("lop3.b32 %0, %1, %2, %3, 0x7E;" : "=r"(r) : "r"(w0()), "r"(w2()), "r"(tag));
        return r;
    }
};
__device__ __forceinline__ void pkt_store(uint4* p, uint32_t a, uint32_t b, uint32_t c, uint32_t d, uint32_t tag) {
    a = (a & ~1u) | tag;
    c = (c & ~1u) | tag;
    asm volatile("{\n.reg .b64 lo, hi;\nmov.b64 lo, {%1,%2};\nmov.b64 hi, {%3,%4};\n"
                 "st.relaxed.gpu.global.v2.b64 [%0], {lo, hi};\n}" ::"l"(p), "r"(a), "r"(b), "r"(c), "r"(d) : "memory");
}
__device__ __forceinline__ uint32_t pack_bf16_tagged(float lo, float hi, uint32_t tag) {
    uint32_t r = pack_bf16(lo, hi);
    if ((r ^ tag) & 1u) {
        const uint32_t mag = r & 0x7fffu;
        const bool up = mag == 0 || (fabsf(lo) > __uint_as_float(mag << 16) && mag < 0x7f7fu);
        r += up ? 1u : 0xffffffffu;
    }
    return r;
}
__device__ __forceinline__ void pkt_load(Pkt& v, const uint4* p) {
    asm volatile("ld.relaxed.gpu.global.v2.b64 {%0, %1}, [%2];" : "=l"(v.lo), "=l"(v.hi) : "l"(p) : "memory");
}
__device__ __forceinline__ void pkt_reload(Pkt& v, const uint4* p, uint32_t bad) {
    asm volatile("{\n.reg .pred p;\n.reg .b32 t;\nand.b32 t, %3, 1;\nsetp.ne.u32 p, t, 0;\n"
                 "@p ld.relaxed.gpu.global.v2.b64 {%0, %1}, [%2];\n}"
                 : "+l"(v.lo), "+l"(v.hi) : "l"(p), "r"(bad) : "memory");
}
__device__ __forceinline__ uint32_t or3(uint32_t a, uint32_t b, uint32_t c) {
    uint32_t r;
    asm("lop3.b32 %0, %1, %2, %3, 0xFE;" : "=r"(r) : "r"(a), "r"(b), "r"(c));
    return r;
}
__device__ __forceinline__ bool any_bit0(uint32_t x) {
    uint32_t r;
    asm volatile("{\n.reg .pred p, q;\n.reg .b32 t;\nand.b32 t, %1, 1;\nsetp.ne.u32 p, t, 0;\nvote.sync.any.pred q, p, 0xffffffff;\n"
                 "selp.u32 %0, 1, 0, q;\n}" : "=r"(r) : "r"(x));
    return r;
}
template <int N, int N0, int S0, int S1>
__device__ __forceinline__ void pkt_issue(Pkt (&v)[N], const uint4* p) {
#pragma unroll
    for (int i = 0; i < N; i++) pkt_load(v[i], p + (i / N0) * S1 + (i % N0) * S0);
}
template <int N, int N0, int S0, int S1>
__device__ __forceinline__ void pkt_poll(Pkt (&v)[N], const uint4* p, uint32_t tag) {
    static_assert(N == 8, "");
#pragma unroll 1
    for (int it = 0;; it++) {
        uint32_t b[N];
#pragma unroll
        for (int i = 0; i < N; i++) b[i] = v[i].bad(tag);
        if (!any_bit0(or3(or3(b[0], b[1], b[2]), or3(b[3], b[4], b[5]), or3(b[6], b[7], 0u)))) break;
#pragma unroll
        for (int i = 0; i < N; i++) pkt_reload(v[i], p + (i / N0) * S1 + (i % N0) * S0, b[i]);
        if (it > (1 << 20)) __trap();
    }
}

__device__ __forceinline__ uint32_t now_ns() {
    uint32_t t;
    asm volatile("mov.u32 %0, %%globaltimer_lo;" : "=r"(t));
    return t;
}
__device__ __forceinline__ void wait_until(uint32_t t) {
#pragma unroll 1
    for (int i = 0; (int)(now_ns() - t) < 0 && i < (1 << 16); i++) {}
}

struct Ptrs { const uint8_t* p[2]; };

__global__ void __cluster_dims__(2, 1, 1) __launch_bounds__(288, 1)
gqa_kernel(const __grid_constant__ Ptrs ptrs, __nv_bfloat16* __restrict__ out, uint32_t slot_ns, uint32_t zero,
           const __grid_constant__ CUtensorMap tmK, const __grid_constant__ CUtensorMap tmV,
           const __grid_constant__ CUtensorMap tmX, const __grid_constant__ CUtensorMap tmWq,
           const __grid_constant__ CUtensorMap tmWo) {
    const uint8_t* const wq = pin(ptrs.p[threadIdx.x >> 10]);
    const uint32_t tstart = now_ns();
    asm volatile("prefetch.tensormap [%0];" ::"l"(&tmWq) : "memory");
    asm volatile("prefetch.tensormap [%0];" ::"l"(&tmK) : "memory");
    if (threadIdx.x == 32)
        asm volatile("cp.async.bulk.prefetch.L2.global [%0], %1;" ::"l"(wq + blockIdx.x * PF_BYTES), "r"(PF_BYTES) : "memory");
    extern __shared__ __align__(1024) uint8_t smem_raw[];
    const uint32_t sb = pin((uint32_t)__cvta_generic_to_shared(smem_raw));
    if (threadIdx.x == 0) {
        mbar_init(sb + BAR_W, 1);
        asm volatile("fence.mbarrier_init.release.cluster;" ::: "memory");
        mbar_expect_tx(sb + BAR_W, 65536);
        tma2d(sb + OFF_WQ, &tmWq, blockIdx.x * 32, 0, sb + BAR_W);
        tma2d(sb + OFF_WQ + 16384, &tmWq, blockIdx.x * 32, 256, sb + BAR_W);
        tma3d(sb + OFF_X, &tmX, 0, 0, 0, sb + BAR_W);
    }
    const int warp = __shfl_sync(0xffffffffu, threadIdx.x >> 5, 0), lane = pin(threadIdx.x & 31);
    const int cta = pin(blockIdx.x), rank = cta & 1, bh = cta >> 1;

    if (warp == 8) {
        const int row0 = bh * 2048 + rank * 64;
        uint64_t pol;
        asm volatile("createpolicy.fractional.L2::evict_first.b64 %0, 1.0;" : "=l"(pol));
        auto issue = [&](int n) {
            const bool isv = n >= 2 * NT - KA || (n >= KA && ((n - KA) & 1));
            const int t = n < KA ? n : n >= 2 * NT - KA ? n - NT : isv ? (n - KA) >> 1 : (n + KA) >> 1;
            const int st = n % NST;
            if (isv) tma2d_hint(sb + st * STAGE, &tmV, rank * 64, bh * 2048 + t * 128, sb + BAR_FULL + 8 * st, pol);
            else tma3d_hint(sb + st * STAGE, &tmK, 0, row0 + t * 128, 0, sb + BAR_FULL + 8 * st, pol);
        };
        if (lane == 0) {
            if (sb & 1023) __trap();
#pragma unroll
            for (int i = 0; i < WIN0; i++) mbar_init(sb + BAR_FULL + 8 * i, 1);
            asm volatile("fence.mbarrier_init.release.cluster;" ::: "memory");
#pragma unroll
            for (int n = 0; n < WIN0; n++) {
                mbar_expect_tx(sb + BAR_FULL + 8 * n, STAGE);
                issue(n);
            }
            for (int i = WIN0; i < NST; i++) mbar_init(sb + BAR_FULL + 8 * i, 1);
            for (int i = 0; i < NST; i++) mbar_init(sb + BAR_EMPTY + 8 * i, 4);
            for (int i = 0; i < NP; i++) {
                mbar_init(sb + BAR_PFULL + 8 * i, 4);
                mbar_init(sb + BAR_PFULL + 8 * (NP + i), 1);
                mbar_expect_tx(sb + BAR_PFULL + 8 * (NP + i), 2048 + 64);
                mbar_init(sb + BAR_PEMPTY + 8 * i, 2);
                mbar_init(sb + BAR_PEMPTY + 8 * (NP + i), 2);
            }
            mbar_init(sb + BAR_STAT, 1);
            mbar_init(sb + BAR_F, 1);
            mbar_init(sb + BAR_D, 4);
            mbar_expect_tx(sb + BAR_STAT, 128);
            for (int i = 0; i < 4; i++) {
                mbar_init(sb + BAR_WO + 8 * i, 1);
                mbar_expect_tx(sb + BAR_WO + 8 * i, 8192);
            }
            asm volatile("fence.mbarrier_init.release.cluster;" ::: "memory");
            asm volatile("prefetch.tensormap [%0];" ::"l"(&tmWo) : "memory");
        }
        __syncwarp();
        asm volatile("bar.arrive 0, 288;" ::: "memory");
        asm volatile("barrier.cluster.arrive.relaxed.aligned;" ::: "memory");
        if (lane == 0) {
            auto wait_free = [&](int n) {
                const int st = n % NST, k = n / NST;
                if (st >= NST0) mbar_wait(sb + BAR_EMPTY + 8 * st, k & 1);
                else if (k) mbar_wait(sb + BAR_EMPTY + 8 * st, (k - 1) & 1);
            };
            const uint32_t t3 = tstart + PA_NS;
#pragma unroll
            for (int n = WIN0; n < 2 * NT; n++) {
                wait_free(n);
                mbar_expect_tx(sb + BAR_FULL + 8 * (n % NST), STAGE);
                if (n < WSW || n >= WSW + WIN - WIN0) {
                    const int d = n - (n < WSW ? WIN0 : WIN);
                    mbar_wait(sb + BAR_FULL + 8 * (d % NST), (d / NST) & 1);
                }
                if (n >= WSW) wait_until(t3 + (n - 3) * slot_ns);
                issue(n);
            }
            wait_free(2 * NT); wait_free(2 * NT + 1); wait_free(2 * NT + 2);
#pragma unroll
            for (int g = 0; g < 4; g++) {
                wait_until(t3 + (WO_SLOT + g * WO_STEP) * slot_ns / 100);
                tma2d(sb + OFF_WO + g * 8192, &tmWo, (cta & 15) * 32, (cta >> 4) * 512 + g * 128, sb + BAR_WO + 8 * g);
            }
        }
        return;
    }

    unsigned epoch;
    asm volatile("ld.relaxed.gpu.global.u32 %0, [%1];" : "=r"(epoch) : "l"(&g_scr.ticket) : "memory");
    epoch >>= 7;
    if (cta < 16 && warp >= 4) {
        const int i = threadIdx.x - 128;
        *reinterpret_cast<uint4*>(out + (i >> 2) * 512 + cta * 32 + (i & 3) * 8) = make_uint4(0, 0, 0, 0);
    }
    const int g8 = lane >> 2, quad = lane & 3;
    const int rh = warp >> 2, g = (warp + 2 * rh) & 3;
    const uint4* const oin = pin(&g_scr.o[((cta >> 4) * 4 + g) * 512 + rh * 64 + lane]);
    uint4* const mine = pin(warp < 4 ? &g_scr.q[cta * 128 + warp * 32 + lane]
                                     : &g_scr.o[(((bh & 7) * 4 + (warp & 2) + (lane >> 4)) * 4 + rank * 2 + (warp & 1)) * 128 +
                                                (bh >> 3) * 16 + (lane & 15)]);
    __nv_bfloat16* const optr = pin(out + (rh * 16 + (g & 1) * 8 + quad * 2 + (g8 & 1)) * 512 + (cta & 15) * 32 + (g >> 1) * 16 +
                                    (g8 & 4) + (g8 & 2) * 4);
    bar_sync(0, 288);

    {
        const int kq = warp & 3, mt = warp >> 2;
        float c[4][4];
#pragma unroll
        for (int j = 0; j < 4; j++) c[j][0] = c[j][1] = c[j][2] = c[j][3] = 0.f;
        const int ar = mt * 16 + (lane & 15);
        const uint32_t abase = sb + OFF_X + kq * 8192 + ar * 128;
        const int br = lane & 15;
        const uint32_t bbase = sb + OFF_WQ + (kq * 128 + br) * 64;
        pkt_store(mine, 0, 0, 0, 0, epoch & 1);
        mbar_wait(sb + BAR_W, 0);
#pragma unroll
        for (int ks = 0; ks < 8; ks++) {
            uint32_t a[4], b0[4], b1[4];
            ldsm4(a, abase + (ks >> 2) * 4096 + ((((ks & 3) * 2 + (lane >> 4)) ^ (ar & 7)) << 4));
            ldsm4t(b0, bbase + ks * 1024 + (((lane >> 4) ^ ((br >> 1) & 3)) << 4));
            ldsm4t(b1, bbase + ks * 1024 + (((2 + (lane >> 4)) ^ ((br >> 1) & 3)) << 4));
            mma(c[0], a, b0[0], b0[1]);
            mma(c[1], a, b0[2], b0[3]);
            mma(c[2], a, b1[0], b1[1]);
            mma(c[3], a, b1[2], b1[3]);
        }
        bar_sync(1, 256);
        asm volatile("barrier.cluster.arrive.relaxed.aligned;" ::: "memory");
        const uint32_t rb = sb + OFF_QRED + (kq * 2 + mt) * 2048 + lane * 16;
        sts128f(rb, c[0][0], c[0][1], c[1][0], c[1][1]);
        sts128f(rb + 512, c[2][0], c[2][1], c[3][0], c[3][1]);
        sts128f(rb + 1024, c[0][2], c[0][3], c[1][2], c[1][3]);
        sts128f(rb + 1536, c[2][2], c[2][3], c[3][2], c[3][3]);
        bar_sync(1, 256);
    }
    const uint32_t tag = pin((epoch + 1) & 1);

    if (warp < 4) {
        {
            const uint32_t rb = sb + OFF_QRED + warp * 1024 + lane * 16;
            float4 s0 = lds128f(rb), s1 = lds128f(rb + 512);
#pragma unroll
            for (int kq = 1; kq < 4; kq++) {
                float4 t0 = lds128f(rb + kq * 4096), t1 = lds128f(rb + kq * 4096 + 512);
                s0.x += t0.x; s0.y += t0.y; s0.z += t0.z; s0.w += t0.w;
                s1.x += t1.x; s1.y += t1.y; s1.z += t1.z; s1.w += t1.w;
            }
            pkt_store(mine, pack_bf16_tagged(s0.x, s0.y, tag), pack_bf16(s0.z, s0.w),
                      pack_bf16_tagged(s1.x, s1.y, tag), pack_bf16(s1.z, s1.w), tag);
            __syncwarp();
            if (lane < NST - NST0) mbar_arrive(sb + BAR_EMPTY + 8 * (NST0 + lane));
        }
        __nanosleep(Q_DELAY_NS);
        uint32_t q[8][4];
        {
            Pkt v[8];
            const uint4* qp = &g_scr.q[(((bh & 7) * 4 + (lane >> 4)) * 4) * 128 + (bh >> 3) * 16 + (lane & 15)];
            pkt_issue<8, 4, 128, 1024>(v, qp);
            pkt_poll<8, 4, 128, 1024>(v, qp, tag);
#pragma unroll
            for (int dq = 0; dq < 4; dq++) {
                const Pkt &a = v[dq], &b = v[4 + dq];
                q[2 * dq][0] = a.w0();     q[2 * dq][1] = b.w0();     q[2 * dq][2] = a.w1();     q[2 * dq][3] = b.w1();
                q[2 * dq + 1][0] = a.w2(); q[2 * dq + 1][1] = b.w2(); q[2 * dq + 1][2] = a.w3(); q[2 * dq + 1][3] = b.w3();
            }
        }
        asm volatile("barrier.cluster.wait.acquire.aligned;" ::: "memory");
        constexpr float C = 0.08838834764831845f * 1.4426950408889634f;
        float mc0 = -INFINITY, mc1 = -INFINITY, l0 = 0.f, l1 = 0.f;
        const int key = warp * 16 + (lane >> 4) * 8 + (lane & 7);
        const uint32_t koff = key * 128;
        const int ksel = (lane >> 3) & 1, kx = lane & 7;
        const uint32_t rp = mapa(sb + OFF_P + NP * 2048 + warp * 512 + lane * 16, rank ^ 1);
        const uint32_t ra = mapa(sb + OFF_ALPHA + NP * 64 + g8 * 4, rank ^ 1), rfull = mapa(sb + BAR_PFULL + 8 * NP, rank ^ 1);
        int st = 0;
        uint32_t par = 0;
#pragma unroll 1
        for (int i = 0; i < NT; i++) {
            const uint32_t kb = sb + st * STAGE + koff;
            float s[2][2][4];
#pragma unroll
            for (int j = 0; j < 4; j++) s[0][0][j] = s[0][1][j] = s[1][0][j] = s[1][1][j] = 0.f;
            mbar_wait(sb + BAR_FULL + 8 * st, par);
#pragma unroll
            for (int ks = 0; ks < 8; ks++) {
                uint32_t b[4];
                ldsm4(b, kb + (ks >> 2) * 8192 + ((((ks & 3) * 2 + ksel) ^ kx) << 4));
                mma(s[ks & 1][0], q[ks], b[0], b[1]);
                mma(s[ks & 1][1], q[ks], b[2], b[3]);
            }
            __syncwarp();
            if (lane == 0) mbar_arrive(sb + BAR_EMPTY + 8 * st);
            st += i < KA ? 1 : 2;
            if (st >= NST) { st -= NST; par ^= 1; }
            float sv[2][4];
#pragma unroll
            for (int j = 0; j < 4; j++) { sv[0][j] = s[0][0][j] + s[1][0][j]; sv[1][j] = s[0][1][j] + s[1][1][j]; }
            float t0 = fmaxf(fmaxf(sv[0][0], sv[0][1]), fmaxf(sv[1][0], sv[1][1]));
            float t1 = fmaxf(fmaxf(sv[0][2], sv[0][3]), fmaxf(sv[1][2], sv[1][3]));
            t0 = fmaxf(t0, __shfl_xor_sync(0xffffffffu, t0, 1));
            t1 = fmaxf(t1, __shfl_xor_sync(0xffffffffu, t1, 1));
            t0 = fmaxf(t0, __shfl_xor_sync(0xffffffffu, t0, 2));
            t1 = fmaxf(t1, __shfl_xor_sync(0xffffffffu, t1, 2));
            const uint32_t wm = sb + OFF_WMAX + (i & 1) * 256 + g8 * 16;
            if (quad == 0) { sts32f(wm + warp * 4, t0); sts32f(wm + 128 + warp * 4, t1); }
            bar_sync(2, 128);
            const float4 w0 = lds128f(wm), w1 = lds128f(wm + 128);
            const float n0 = fmaxf(mc0, fmaxf(fmaxf(w0.x, w0.y), fmaxf(w0.z, w0.w)) * C);
            const float n1 = fmaxf(mc1, fmaxf(fmaxf(w1.x, w1.y), fmaxf(w1.z, w1.w)) * C);
            const float a0 = ex2(mc0 - n0), a1 = ex2(mc1 - n1);
            mc0 = n0; mc1 = n1;
            float p[2][4];
#pragma unroll
            for (int j = 0; j < 2; j++) {
                p[j][0] = ex2(fmaf(sv[j][0], C, -n0)); p[j][1] = ex2(fmaf(sv[j][1], C, -n0));
                p[j][2] = ex2(fmaf(sv[j][2], C, -n1)); p[j][3] = ex2(fmaf(sv[j][3], C, -n1));
            }
            l0 = l0 * a0 + ((p[0][0] + p[0][1]) + (p[1][0] + p[1][1]));
            l1 = l1 * a1 + ((p[0][2] + p[0][3]) + (p[1][2] + p[1][3]));
            const int slot = i % NP;
            if (i >= NP) {
                mbar_wait(sb + BAR_PEMPTY + 8 * slot, (i / NP - 1) & 1);
                mbar_wait(sb + BAR_PEMPTY + 8 * (NP + slot), (i / NP - 1) & 1);
            }
            const uint32_t p0 = pack_bf16(p[0][0], p[0][1]), p1 = pack_bf16(p[0][2], p[0][3]), p2 = pack_bf16(p[1][0], p[1][1]),
                           p3 = pack_bf16(p[1][2], p[1][3]);
            asm volatile("st.async.weak.shared::cluster.mbarrier::complete_tx::bytes.v4.b32 [%0], {%1,%2,%3,%4}, [%5];"
                         ::"r"(rp + slot * 2048), "r"(p1), "r"(p0), "r"(p3), "r"(p2), "r"(rfull + 8 * slot) : "memory");
            sts128(sb + OFF_P + slot * 2048 + warp * 512 + lane * 16, p0, p1, p2, p3);
            if (warp == 0 && quad == 0) {
                asm volatile("st.async.weak.shared::cluster.mbarrier::complete_tx::bytes.f32 [%0], %1, [%2];"
                             ::"r"(ra + slot * 64), "f"(a1), "r"(rfull + 8 * slot) : "memory");
                asm volatile("st.async.weak.shared::cluster.mbarrier::complete_tx::bytes.f32 [%0], %1, [%2];"
                             ::"r"(ra + slot * 64 + 32), "f"(a0), "r"(rfull + 8 * slot) : "memory");
                sts32f(sb + OFF_ALPHA + slot * 64 + g8 * 4, a0);
                sts32f(sb + OFF_ALPHA + slot * 64 + 32 + g8 * 4, a1);
            }
            __syncwarp();
            if (lane == 0) mbar_arrive(sb + BAR_PFULL + 8 * slot);
        }
        l0 += __shfl_xor_sync(0xffffffffu, l0, 1);
        l1 += __shfl_xor_sync(0xffffffffu, l1, 1);
        l0 += __shfl_xor_sync(0xffffffffu, l0, 2);
        l1 += __shfl_xor_sync(0xffffffffu, l1, 2);
        if (quad == 0) {
            sts32f(sb + OFF_LSUM + g8 * 16 + warp * 4, l0);
            sts32f(sb + OFF_LSUM + 128 + g8 * 16 + warp * 4, l1);
            if (warp == 0) { sts32f(sb + OFF_MROW + g8 * 4, mc0); sts32f(sb + OFF_MROW + 32 + g8 * 4, mc1); }
        }
        bar_sync(2, 128);
        if (warp == 0) {
            if (lane < 16) {
                const float4 lv = lds128f(sb + OFF_LSUM + lane * 16);
                const float l = (lv.x + lv.y) + (lv.z + lv.w), m = lds32f(sb + OFF_MROW + lane * 4);
                asm volatile("st.async.weak.shared::cluster.mbarrier::complete_tx::bytes.v2.f32 [%0], {%1,%2}, [%3];"
                             ::"r"(mapa(sb + OFF_STAT + lane * 8, rank ^ 1)), "f"(m), "f"(l), "r"(mapa(sb + BAR_STAT, rank ^ 1)) : "memory");
                mbar_wait(sb + BAR_STAT, 0);
                const float pm = lds32f(sb + OFF_STAT + lane * 8), pl = lds32f(sb + OFF_STAT + lane * 8 + 4);
                const float mm = fmaxf(m, pm);
                const float e = ex2(m - mm), pe = ex2(pm - mm);
                const float inv = __fdividef(1.f, rank ? pl * pe + l * e : l * e + pl * pe);
                sts32f(sb + OFF_F + lane * 4, e * inv);
                sts32f(sb + OFF_F + 64 + (lane ^ 8) * 4, pe * inv);
            }
            __syncwarp();
            if (lane == 0) mbar_arrive(sb + BAR_F);
        }
        mbar_wait(sb + BAR_D, 0);
    } else {
        const int w = warp - 4;
        asm volatile("barrier.cluster.wait.acquire.aligned;" ::: "memory");
        if (threadIdx.x == 128) {
            asm volatile("red.relaxed.gpu.global.add.u32 [%0], 1;" ::"l"(&g_scr.ticket) : "memory");
            if (cta < 16) asm volatile("st.release.gpu.global.u32 [%0], %1;" ::"l"(&g_scr.zeroed[cta * 32]), "r"(epoch + 1) : "memory");
            unsigned z;
#pragma unroll 1
            for (int it = 0;; it++) {
                asm volatile("ld.acquire.gpu.global.u32 %0, [%1];" : "=r"(z) : "l"(&g_scr.zeroed[(cta & 15) * 32]) : "memory");
                if (z == epoch + 1) break;
                if (it > (1 << 20)) __trap();
                __nanosleep(200);
            }
        }
        __syncwarp();
        const int src = w >> 1, ds = w & 1;
        const uint32_t pbase = pin(sb + OFF_P + src * NP * 2048 + lane * 16), abase = pin(sb + OFF_ALPHA + src * NP * 64 + g8 * 4);
        const uint32_t pfull = pin(sb + BAR_PFULL + src * NP * 8);
        const uint32_t pempty = src ? mapa(sb + BAR_PEMPTY + 8 * NP, rank ^ 1) : mapa(sb + BAR_PEMPTY, rank);
        float o[4][4], t[2][4][4];
#pragma unroll
        for (int j = 0; j < 16; j++) (&o[0][0])[j] = (&t[0][0][0])[j] = (&t[1][0][0])[j] = 0.f;
        const uint32_t voff = ((rank ^ src) * 64 + (lane & 15)) * 128;
        const int vc = ds * 4 + (lane >> 4), vx = lane & 7;
        const uint32_t v0 = pin(sb + voff + ((vc ^ vx) << 4)), v1 = pin(sb + voff + (((vc + 2) ^ vx) << 4));
        uint32_t p[4][4], b0[4][4], b1[4][4];
        float a0 = 0.f, a1 = 0.f;
        auto load_v = [&](int st) {
#pragma unroll
            for (int j = 0; j < 4; j++) {
                ldsm4t(b0[j], v0 + st * STAGE + j * 2048);
                ldsm4t(b1[j], v1 + st * STAGE + j * 2048);
            }
        };
        auto next_p = [&](int i) {
            const int slot = i % NP;
            mbar_wait(pfull + 8 * slot, (i / NP) & 1);
#pragma unroll
            for (int j = 0; j < 4; j++) lds128(p[j], pbase + slot * 2048 + j * 512);
            const float n0 = lds32f(abase + slot * 64), n1 = lds32f(abase + slot * 64 + 32);
            __syncwarp();
            if (lane == 0 && i < NT - NP) {
                if (w == 2) mbar_expect_tx(pfull + 8 * slot, 2048 + 64);
                asm volatile("mbarrier.arrive.relaxed.cluster.shared::cluster.b64 _, [%0];"
                             ::"r"(pempty + 8 * slot + ((p[3][3] | __float_as_uint(n1)) & zero)) : "memory");
            }
#pragma unroll
            for (int j = 0; j < 4; j++) {
                o[j][0] = fmaf(o[j][0], a0, t[0][j][0] + t[1][j][0]); o[j][1] = fmaf(o[j][1], a0, t[0][j][1] + t[1][j][1]);
                o[j][2] = fmaf(o[j][2], a1, t[0][j][2] + t[1][j][2]); o[j][3] = fmaf(o[j][3], a1, t[0][j][3] + t[1][j][3]);
            }
            a0 = n0; a1 = n1;
        };
        auto pv = [&]() {
#pragma unroll
            for (int j = 0; j < 16; j++) (&t[0][0][0])[j] = (&t[1][0][0])[j] = 0.f;
#pragma unroll
            for (int j = 0; j < 4; j++) {
                mma(t[j & 1][0], p[j], b0[j][0], b0[j][1]);
                mma(t[j & 1][1], p[j], b0[j][2], b0[j][3]);
                mma(t[j & 1][2], p[j], b1[j][0], b1[j][1]);
                mma(t[j & 1][3], p[j], b1[j][2], b1[j][3]);
            }
        };
        int st = KA + 1;
        uint32_t par = 0;
#pragma unroll 1
        for (int i = 0; i < NT - 1; i++) {
            mbar_wait(sb + BAR_FULL + 8 * st, par);
            load_v(st);
            next_p(i);
            pv();
            __syncwarp();
            if (lane == 0) mbar_arrive(sb + BAR_EMPTY + 8 * st);
            st += i < NT - KA - 1 ? 2 : 1;
            if (st >= NST) { st -= NST; par ^= 1; }
        }
        constexpr int LST = (2 * NT - 1) % NST, LPAR = ((2 * NT - 1) / NST) & 1;
        const bool landed = mbar_test(sb + BAR_FULL + 8 * LST, LPAR);
        if (landed) load_v(LST);
        next_p(NT - 1);
        mbar_wait(sb + BAR_F, 0);
        const float f0 = lds32f(sb + OFF_F + src * 64 + g8 * 4), f1 = lds32f(sb + OFF_F + src * 64 + 32 + g8 * 4);
        a0 *= f0; a1 *= f1;
#pragma unroll
        for (int j = 0; j < 4; j++) {
            o[j][0] *= a0; o[j][1] *= a0; o[j][2] *= a1; o[j][3] *= a1;
            asm volatile("" : "+f"(o[j][0]), "+f"(o[j][1]), "+f"(o[j][2]), "+f"(o[j][3]));
        }
        if (!landed) {
            mbar_wait(sb + BAR_FULL + 8 * LST, LPAR);
            load_v(LST);
        }
        pv();
#pragma unroll
        for (int j = 0; j < 4; j++) {
            o[j][0] = fmaf(t[0][j][0] + t[1][j][0], f0, o[j][0]); o[j][1] = fmaf(t[0][j][1] + t[1][j][1], f0, o[j][1]);
            o[j][2] = fmaf(t[0][j][2] + t[1][j][2], f1, o[j][2]); o[j][3] = fmaf(t[0][j][3] + t[1][j][3], f1, o[j][3]);
        }
        {
            const uint32_t ours = sb + OFF_MERGE + w * 1024 + lane * 16, theirs = sb + OFF_MERGE + (w ^ 2) * 1024 + lane * 16;
            sts128f(theirs, o[0][2], o[0][3], o[1][2], o[1][3]);
            sts128f(theirs + 512, o[2][2], o[2][3], o[3][2], o[3][3]);
            bar_sync(5 + ds, 64);
            const float4 r0 = lds128f(ours), r1 = lds128f(ours + 512);
            pkt_store(mine, pack_bf16(o[0][0] + r0.x, o[0][1] + r0.y), pack_bf16(o[1][0] + r0.z, o[1][1] + r0.w),
                      pack_bf16(o[2][0] + r1.x, o[2][1] + r1.y), pack_bf16(o[3][0] + r1.z, o[3][1] + r1.w), tag);
        }
        if (lane == 0) mbar_arrive(sb + BAR_D);
    }

    {
        uint32_t a[8][2][4];
        const int kr = (lane >> 4) * 8 + (lane & 7);
        const int wc = (lane >> 3) & 1, wx = (kr >> 1) & 3;
        const uint32_t wb0 = pin(sb + OFF_WO + (g * 128 + kr) * 64 + ((wc ^ wx) << 4));
        const uint32_t wb1 = pin(sb + OFF_WO + (g * 128 + kr) * 64 + (((wc + 2) ^ wx) << 4));
        const uint32_t red = pin(sb + OFF_PRED + rh * 8192 + lane * 16);
        const uint32_t rw = pin(red + g * 512), rr = pin(red + (g & 1) * 4096 + (g >> 1) * 2048);
        const uint32_t wobar = sb + BAR_WO + 8 * g;
        constexpr uint32_t wopar = 0;
        auto wo_within = [&](uint32_t clks) {
            uint32_t c0, c1;
            bool in;
            asm volatile("mov.u32 %0, %%clock;" : "=r"(c0));
            do {
                in = mbar_test(wobar, wopar);
                asm volatile("mov.u32 %0, %%clock;" : "=r"(c1));
            } while (!in && c1 - c0 < clks);
            return in;
        };
        Pkt v[8];
        const bool in0 = wo_within(O_DELAY);
        pkt_issue<8, 4, 128, 32>(v, oin);
        if (!in0) {
#pragma unroll 1
            for (int it = 0; !wo_within(O_PERIOD); it++) {
                uint32_t b[8];
#pragma unroll
                for (int i = 0; i < 8; i++) b[i] = v[i].bad(tag);
                if (it > (1 << 16)) __trap();
#pragma unroll
                for (int i = 0; i < 8; i++) pkt_reload(v[i], oin + (i >> 2) * 32 + (i & 3) * 128, b[i]);
            }
        }
#pragma unroll
        for (int ks = 0; ks < 8; ks++) {
            ldsm4t(a[ks][0], wb0 + ks * 1024);
            ldsm4t(a[ks][1], wb1 + ks * 1024);
        }
        pkt_poll<8, 4, 128, 32>(v, oin, tag | (a[7][1][3] & zero));
        float c[2][2][2][4];
#pragma unroll
        for (int j = 0; j < 32; j++) (&c[0][0][0][0])[j] = 0.f;
#pragma unroll
        for (int dq = 0; dq < 4; dq++)
#pragma unroll
            for (int t = 0; t < 2; t++) {
                mma(c[t][0][0], a[2 * dq][0], v[t * 4 + dq].w0(), v[t * 4 + dq].w1());
                mma(c[t][1][0], a[2 * dq][1], v[t * 4 + dq].w0(), v[t * 4 + dq].w1());
                mma(c[t][0][1], a[2 * dq + 1][0], v[t * 4 + dq].w2(), v[t * 4 + dq].w3());
                mma(c[t][1][1], a[2 * dq + 1][1], v[t * 4 + dq].w2(), v[t * 4 + dq].w3());
            }
#pragma unroll
        for (int t = 0; t < 2; t++)
#pragma unroll
            for (int mt = 0; mt < 2; mt++)
                sts128f(rw + t * 4096 + mt * 2048, c[t][mt][0][0] + c[t][mt][1][0], c[t][mt][0][1] + c[t][mt][1][1],
                        c[t][mt][0][2] + c[t][mt][1][2], c[t][mt][0][3] + c[t][mt][1][3]);
        bar_sync(3 + rh, 128);
        const float4 s0 = lds128f(rr), s1 = lds128f(rr + 512), s2 = lds128f(rr + 1024), s3 = lds128f(rr + 1536);
        const uint32_t r0 = pack_bf16((s0.x + s1.x) + (s2.x + s3.x), (s0.z + s1.z) + (s2.z + s3.z));
        const uint32_t r1 = pack_bf16((s0.y + s1.y) + (s2.y + s3.y), (s0.w + s1.w) + (s2.w + s3.w));
        const bool odd = g8 & 1;
        const uint32_t got = __shfl_xor_sync(0xffffffffu, odd ? r0 : r1, 4);
        const uint32_t lo = odd ? got : r0, hi = odd ? r1 : got;
        const uint32_t w0 = __byte_perm(lo, hi, 0x5410), w1 = __byte_perm(lo, hi, 0x7632);
        const bool up = g8 & 2;
        const uint32_t got2 = __shfl_xor_sync(0xffffffffu, up ? w0 : w1, 8);
        asm volatile("red.relaxed.gpu.global.add.noftz.v2.bf16x2 [%0], {%1, %2};" ::"l"(optr), "r"(up ? got2 : w0), "r"(up ? w1 : got2) : "memory");
    }

}

__global__ void fb_proj(const __nv_bfloat16* a_bf, const float* a_f, const __nv_bfloat16* w, int K, int N, float* o_f,
                        __nv_bfloat16* o_bf) {
    const int c = blockIdx.x * blockDim.x + threadIdx.x, r = blockIdx.y;
    float s = 0.f;
    for (int k = 0; k < K; k++) s += (a_bf ? __bfloat162float(a_bf[r * K + k]) : a_f[r * K + k]) * __bfloat162float(w[k * N + c]);
    if (o_bf) o_bf[r * N + c] = __float2bfloat16(s);
    else o_f[r * N + c] = __bfloat162float(__float2bfloat16(s));
}
__global__ void fb_attn(const __nv_bfloat16* kc, const __nv_bfloat16* vc) {
    __shared__ float sc[2048], red[128];
    const int r = blockIdx.x, hq = blockIdx.y, t = threadIdx.x;
    const size_t base = (size_t)((r >> 2) * 8 + (hq >> 2)) * 2048 * 128;
    float m = -INFINITY, l = 0.f, acc = 0.f;
    for (int j = t; j < 2048; j += 128) {
        float s = 0.f;
        for (int d = 0; d < 128; d++) s += g_scr.fq[r * 4096 + hq * 128 + d] * __bfloat162float(kc[base + j * 128 + d]);
        sc[j] = s * 0.08838834764831845f;
        m = fmaxf(m, sc[j]);
    }
    red[t] = m;
    __syncthreads();
    for (int i = 0; i < 128; i++) m = fmaxf(m, red[i]);
    for (int j = t; j < 2048; j += 128) sc[j] = __expf(sc[j] - m);
    __syncthreads();
    for (int j = 0; j < 2048; j++) {
        l += sc[j];
        acc += sc[j] * __bfloat162float(vc[base + j * 128 + t]);
    }
    g_scr.fo[r * 4096 + hq * 128 + t] = __bfloat162float(__float2bfloat16(acc / l));
}

typedef CUresult (*EncodeFn)(CUtensorMap*, CUtensorMapDataType, cuuint32_t, void*, const cuuint64_t*, const cuuint64_t*,
                             const cuuint32_t*, const cuuint32_t*, CUtensorMapInterleave, CUtensorMapSwizzle,
                             CUtensorMapL2promotion, CUtensorMapFloatOOBfill);

static void encode(EncodeFn fn, CUtensorMap* m, void* p, int rank, const cuuint64_t* dims, const cuuint64_t* strides,
                   const cuuint32_t* box, CUtensorMapSwizzle sw) {
    const cuuint32_t es[3] = {1, 1, 1};
    fn(m, CU_TENSOR_MAP_DATA_TYPE_BFLOAT16, rank, p, dims, strides, box, es, CU_TENSOR_MAP_INTERLEAVE_NONE, sw,
       CU_TENSOR_MAP_L2_PROMOTION_L2_256B, CU_TENSOR_MAP_FLOAT_OOB_FILL_NONE);
}

}

extern "C" void kernel_launch(void* const* d_in, const int* in_sizes, int n_in, void* d_out, int out_size) {
    using namespace gqa;
    static EncodeFn fn = nullptr;
    static uint32_t slot_ns = SLOT_NS;
    static bool fits = false;
    if (!fn) {
        int dev = 0, khz = 0, bits = 0;
        cudaGetDevice(&dev);
        cudaDeviceGetAttribute(&khz, cudaDevAttrMemoryClockRate, dev);
        cudaDeviceGetAttribute(&bits, cudaDevAttrGlobalMemoryBusWidth, dev);
        if (khz > 0 && bits > 0) slot_ns = (uint32_t)((double)NCTA * STAGE / (0.955 * 2.0 * khz * 1e-6 * (bits / 8)));
        void* p = nullptr;
        cudaDriverEntryPointQueryResult qr;
        cudaGetDriverEntryPoint("cuTensorMapEncodeTiled", &p, cudaEnableDefault, &qr);
        fn = (EncodeFn)p;
        cudaFuncSetAttribute(gqa_kernel, cudaFuncAttributeMaxDynamicSharedMemorySize, SMEM_BYTES);
        cudaLaunchConfig_t cfg = {};
        cfg.gridDim = dim3(NCTA);
        cfg.blockDim = dim3(288);
        cfg.dynamicSmemBytes = SMEM_BYTES;
        int clusters = 0;
        fits = cudaOccupancyMaxActiveClusters(&clusters, gqa_kernel, &cfg) == cudaSuccess && clusters >= NCTA / 2;
    }
    if (!fits) {
        Scratch* scr = nullptr;
        cudaGetSymbolAddress((void**)&scr, g_scr);
        float *fq = scr->fq, *fo = scr->fo;
        fb_proj<<<dim3(16, 32), 256, 0, cudaStreamPerThread>>>((const __nv_bfloat16*)d_in[0], nullptr, (const __nv_bfloat16*)d_in[3], 512,
                                                               4096, fq, nullptr);
        fb_attn<<<dim3(32, 32), 128, 0, cudaStreamPerThread>>>((const __nv_bfloat16*)d_in[1], (const __nv_bfloat16*)d_in[2]);
        fb_proj<<<dim3(2, 32), 256, 0, cudaStreamPerThread>>>(nullptr, fo, (const __nv_bfloat16*)d_in[4], 4096, 512, nullptr,
                                                              (__nv_bfloat16*)d_out);
        return;
    }
    CUtensorMap tmK, tmV, tmX, tmWq, tmWo;
    {
        const cuuint64_t dims[3] = {64, 8 * 8 * 2048, 2}, str[2] = {256, 128};
        const cuuint32_t box[3] = {64, 64, 2};
        encode(fn, &tmK, d_in[1], 3, dims, str, box, CU_TENSOR_MAP_SWIZZLE_128B);
        const cuuint64_t dv[2] = {128, 8 * 8 * 2048}, sv[1] = {256};
        const cuuint32_t bv[2] = {64, 128};
        encode(fn, &tmV, d_in[2], 2, dv, sv, bv, CU_TENSOR_MAP_SWIZZLE_128B);
    }
    {
        const cuuint64_t dims[3] = {64, 32, 8}, str[2] = {1024, 128};
        const cuuint32_t box[3] = {64, 32, 8};
        encode(fn, &tmX, d_in[0], 3, dims, str, box, CU_TENSOR_MAP_SWIZZLE_128B);
    }
    {
        const cuuint64_t dq[2] = {4096, 512}, sq[1] = {8192}, dw[2] = {512, 4096}, sw[1] = {1024};
        const cuuint32_t box[2] = {32, 256};
        encode(fn, &tmWq, d_in[3], 2, dq, sq, box, CU_TENSOR_MAP_SWIZZLE_64B);
        const cuuint32_t boxo[2] = {32, 128};
        encode(fn, &tmWo, d_in[4], 2, dw, sw, boxo, CU_TENSOR_MAP_SWIZZLE_64B);
    }
    gqa_kernel<<<NCTA, 288, SMEM_BYTES, cudaStreamPerThread>>>(Ptrs{{(const uint8_t*)d_in[3], nullptr}}, (__nv_bfloat16*)d_out, slot_ns, 0u, tmK, tmV, tmX,
                                                               tmWq, tmWo);
}
```

```cpp
#include <cuda_runtime.h>
#include <cuda_bf16.h>
#include <cuda.h>
#include <stdint.h>

namespace gqa {

constexpr int PA_NS = 2780;
constexpr int SLOT_NS = 655;
constexpr int WO_SLOT = 2880;
constexpr int WO_STEP = 65;
constexpr int Q_DELAY_NS = 1000;
constexpr int O_DELAY = 1000;
constexpr int O_PERIOD = 350;
constexpr int PF_BYTES = 8192;

constexpr int NCTA = 128;
constexpr int NT = 16;
constexpr int NST = 13;
constexpr int NST0 = 10;
constexpr int WIN0 = 3;
constexpr int WIN = 8;
constexpr int WSW = 8;
constexpr int KA = 2;
constexpr int NP = 4;
constexpr int STAGE = 16384;

constexpr int OFF_WQ = NST0 * STAGE;
constexpr int OFF_X = OFF_WQ + 32768;
constexpr int OFF_QRED = OFF_X;
constexpr int OFF_WO = ((2 * NT) % NST) * STAGE;
constexpr int OFF_P = NST * STAGE;
constexpr int OFF_MERGE = (((2 * NT) % NST) + 3) * STAGE + 8192;
constexpr int OFF_ALPHA = (NST + 1) * STAGE + 512;
constexpr int OFF_WMAX = OFF_ALPHA + 2 * NP * 64;
constexpr int OFF_LSUM = OFF_WMAX + 512;
constexpr int OFF_MROW = OFF_LSUM + 256;
constexpr int OFF_STAT = OFF_MROW + 64;
constexpr int OFF_F = OFF_STAT + 128;
constexpr int OFF_PRED = (((2 * NT) % NST) + 2) * STAGE;
constexpr int OFF_BAR = (NST + 1) * STAGE;
constexpr int BAR_FULL = OFF_BAR;
constexpr int BAR_EMPTY = BAR_FULL + 8 * NST;
constexpr int BAR_PFULL = BAR_EMPTY + 8 * NST;
constexpr int BAR_PEMPTY = BAR_PFULL + 16 * NP;
constexpr int BAR_W = BAR_PEMPTY + 16 * NP;
constexpr int BAR_STAT = BAR_W + 8;
constexpr int BAR_F = BAR_STAT + 8;
constexpr int BAR_D = BAR_F + 8;
constexpr int BAR_WO = BAR_D + 8;
constexpr int SMEM_BYTES = OFF_F + 128;
static_assert(2 * NP * 2048 <= STAGE, "P slots overflow");
static_assert(BAR_WO + 32 <= OFF_ALPHA, "barriers overflow");
static_assert((2 * NT) % NST + 3 < NST, "wo / partial slots must not wrap");
static_assert(SMEM_BYTES <= 232448, "too much shared memory");

struct __align__(1024) Scratch {
    uint4 q[32 * 4 * 8 * 16];
    uint4 o[32 * 4 * 8 * 16];
    unsigned ticket;
    unsigned pad[31];
    unsigned zeroed[16 * 32];
    float fq[32 * 4096], fo[32 * 4096];
};
__device__ Scratch g_scr;

__device__ __forceinline__ void mbar_init(uint32_t bar, uint32_t cnt) {
    asm volatile("mbarrier.init.shared::cta.b64 [%0], %1;" ::"r"(bar), "r"(cnt) : "memory");
}
__device__ __forceinline__ void mbar_expect_tx(uint32_t bar, uint32_t bytes) {
    asm volatile("mbarrier.arrive.expect_tx.shared::cta.b64 _, [%0], %1;" ::"r"(bar), "r"(bytes) : "memory");
}
__device__ __forceinline__ void mbar_arrive(uint32_t bar) {
    asm volatile("mbarrier.arrive.shared::cta.b64 _, [%0];" ::"r"(bar) : "memory");
}
__device__ __forceinline__ bool mbar_try(uint32_t bar, uint32_t parity) {
    uint32_t ok;
    asm volatile("{\n.reg .pred p;\nmbarrier.try_wait.parity.shared::cta.b64 p, [%1], %2;\nselp.u32 %0, 1, 0, p;\n}"
                 : "=r"(ok) : "r"(bar), "r"(parity) : "memory");
    return ok;
}
__device__ __forceinline__ bool mbar_test(uint32_t bar, uint32_t parity) {
    uint32_t ok;
    asm volatile("{\n.reg .pred p;\nmbarrier.test_wait.parity.shared::cta.b64 p, [%1], %2;\nselp.u32 %0, 1, 0, p;\n}"
                 : "=r"(ok) : "r"(bar), "r"(parity) : "memory");
    return ok;
}
__device__ __forceinline__ void mbar_wait(uint32_t bar, uint32_t parity) {
#pragma unroll 1
    for (int i = 0; !mbar_try(bar, parity); i++)
        if (i > (1 << 20)) __trap();
}
__device__ __forceinline__ void tma2d(uint32_t dst, const CUtensorMap* m, int c0, int c1, uint32_t bar) {
    asm volatile("cp.async.bulk.tensor.2d.shared::cluster.global.mbarrier::complete_tx::bytes [%0], [%1, {%3, %4}], [%2];"
                 ::"r"(dst), "l"(m), "r"(bar), "r"(c0), "r"(c1) : "memory");
}
__device__ __forceinline__ void tma3d(uint32_t dst, const CUtensorMap* m, int c0, int c1, int c2, uint32_t bar) {
    asm volatile("cp.async.bulk.tensor.3d.shared::cluster.global.mbarrier::complete_tx::bytes [%0], [%1, {%3, %4, %5}], [%2];"
                 ::"r"(dst), "l"(m), "r"(bar), "r"(c0), "r"(c1), "r"(c2) : "memory");
}
__device__ __forceinline__ void tma2d_hint(uint32_t dst, const CUtensorMap* m, int c0, int c1, uint32_t bar, uint64_t pol) {
    asm volatile("cp.async.bulk.tensor.2d.shared::cluster.global.mbarrier::complete_tx::bytes.L2::cache_hint [%0], [%1, {%3, %4}], [%2], %5;"
                 ::"r"(dst), "l"(m), "r"(bar), "r"(c0), "r"(c1), "l"(pol) : "memory");
}
__device__ __forceinline__ uint32_t mapa(uint32_t addr, uint32_t cta_rank) {
    uint32_t r;
    asm("mapa.shared::cluster.u32 %0, %1, %2;" : "=r"(r) : "r"(addr), "r"(cta_rank));
    return r;
}
__device__ __forceinline__ void tma3d_hint(uint32_t dst, const CUtensorMap* m, int c0, int c1, int c2, uint32_t bar, uint64_t pol) {
    asm volatile("cp.async.bulk.tensor.3d.shared::cluster.global.mbarrier::complete_tx::bytes.L2::cache_hint [%0], [%1, {%3, %4, %5}], [%2], %6;"
                 ::"r"(dst), "l"(m), "r"(bar), "r"(c0), "r"(c1), "r"(c2), "l"(pol) : "memory");
}
__device__ __forceinline__ void ldsm4(uint32_t (&r)[4], uint32_t addr) {
    asm volatile("ldmatrix.sync.aligned.m8n8.x4.shared.b16 {%0,%1,%2,%3}, [%4];"
                 : "=r"(r[0]), "=r"(r[1]), "=r"(r[2]), "=r"(r[3]) : "r"(addr) : "memory");
}
__device__ __forceinline__ void ldsm4t(uint32_t (&r)[4], uint32_t addr) {
    asm volatile("ldmatrix.sync.aligned.m8n8.x4.trans.shared.b16 {%0,%1,%2,%3}, [%4];"
                 : "=r"(r[0]), "=r"(r[1]), "=r"(r[2]), "=r"(r[3]) : "r"(addr) : "memory");
}
__device__ __forceinline__ void mma(float (&c)[4], const uint32_t (&a)[4], uint32_t b0, uint32_t b1) {
    asm volatile("mma.sync.aligned.m16n8k16.row.col.f32.bf16.bf16.f32 {%0,%1,%2,%3}, {%4,%5,%6,%7}, {%8,%9}, {%0,%1,%2,%3};"
                 : "+f"(c[0]), "+f"(c[1]), "+f"(c[2]), "+f"(c[3])
                 : "r"(a[0]), "r"(a[1]), "r"(a[2]), "r"(a[3]), "r"(b0), "r"(b1));
}
__device__ __forceinline__ uint32_t pack_bf16(float lo, float hi) {
    uint32_t r;
    asm("cvt.rn.bf16x2.f32 %0, %1, %2;" : "=r"(r) : "f"(hi), "f"(lo));
    return r;
}
__device__ __forceinline__ float ex2(float x) {
    float y;
    asm("ex2.approx.ftz.f32 %0, %1;" : "=f"(y) : "f"(x));
    return y;
}
__device__ __forceinline__ void sts128(uint32_t addr, uint32_t a, uint32_t b, uint32_t c, uint32_t d) {
    asm volatile("st.shared.v4.b32 [%0], {%1,%2,%3,%4};" ::"r"(addr), "r"(a), "r"(b), "r"(c), "r"(d) : "memory");
}
__device__ __forceinline__ void sts128f(uint32_t addr, float a, float b, float c, float d) {
    asm volatile("st.shared.v4.f32 [%0], {%1,%2,%3,%4};" ::"r"(addr), "f"(a), "f"(b), "f"(c), "f"(d) : "memory");
}
__device__ __forceinline__ void sts32f(uint32_t addr, float a) {
    asm volatile("st.shared.f32 [%0], %1;" ::"r"(addr), "f"(a) : "memory");
}
__device__ __forceinline__ void lds128(uint32_t (&r)[4], uint32_t addr) {
    asm volatile("ld.shared.v4.b32 {%0,%1,%2,%3}, [%4];" : "=r"(r[0]), "=r"(r[1]), "=r"(r[2]), "=r"(r[3]) : "r"(addr) : "memory");
}
__device__ __forceinline__ float4 lds128f(uint32_t addr) {
    float4 v;
    asm volatile("ld.shared.v4.f32 {%0,%1,%2,%3}, [%4];" : "=f"(v.x), "=f"(v.y), "=f"(v.z), "=f"(v.w) : "r"(addr) : "memory");
    return v;
}
__device__ __forceinline__ float lds32f(uint32_t addr) {
    float v;
    asm volatile("ld.shared.f32 %0, [%1];" : "=f"(v) : "r"(addr) : "memory");
    return v;
}
__device__ __forceinline__ void bar_sync(int id, int n) { asm volatile("bar.sync %0, %1;" ::"r"(id), "r"(n) : "memory"); }
template <typename T> __device__ __forceinline__ T* pin(T* p) { asm volatile("" : "+l"(p)); return p; }
__device__ __forceinline__ uint32_t pin(uint32_t v) { asm volatile("" : "+r"(v)); return v; }

struct Pkt {
    uint64_t lo, hi;
    __device__ __forceinline__ uint32_t w0() const { return (uint32_t)lo; }
    __device__ __forceinline__ uint32_t w1() const { return (uint32_t)(lo >> 32); }
    __device__ __forceinline__ uint32_t w2() const { return (uint32_t)hi; }
    __device__ __forceinline__ uint32_t w3() const { return (uint32_t)(hi >> 32); }
    __device__ __forceinline__ uint32_t bad(uint32_t tag) const {
        uint32_t r;
        asm("lop3.b32 %0, %1, %2, %3, 0x7E;" : "=r"(r) : "r"(w0()), "r"(w2()), "r"(tag));
        return r;
    }
};
__device__ __forceinline__ void pkt_store(uint4* p, uint32_t a, uint32_t b, uint32_t c, uint32_t d, uint32_t tag) {
    a = (a & ~1u) | tag;
    c = (c & ~1u) | tag;
    asm volatile("{\n.reg .b64 lo, hi;\nmov.b64 lo, {%1,%2};\nmov.b64 hi, {%3,%4};\n"
                 "st.relaxed.gpu.global.v2.b64 [%0], {lo, hi};\n}" ::"l"(p), "r"(a), "r"(b), "r"(c), "r"(d) : "memory");
}
__device__ __forceinline__ uint32_t pack_bf16_tagged(float lo, float hi, uint32_t tag) {
    uint32_t r = pack_bf16(lo, hi);
    if ((r ^ tag) & 1u) {
        const uint32_t mag = r & 0x7fffu;
        const bool up = mag == 0 || (fabsf(lo) > __uint_as_float(mag << 16) && mag < 0x7f7fu);
        r += up ? 1u : 0xffffffffu;
    }
    return r;
}
__device__ __forceinline__ void pkt_load(Pkt& v, const uint4* p) {
    asm volatile("ld.relaxed.gpu.global.v2.b64 {%0, %1}, [%2];" : "=l"(v.lo), "=l"(v.hi) : "l"(p) : "memory");
}
__device__ __forceinline__ void pkt_reload(Pkt& v, const uint4* p, uint32_t bad) {
    asm volatile("{\n.reg .pred p;\n.reg .b32 t;\nand.b32 t, %3, 1;\nsetp.ne.u32 p, t, 0;\n"
                 "@p ld.relaxed.gpu.global.v2.b64 {%0, %1}, [%2];\n}"
                 : "+l"(v.lo), "+l"(v.hi) : "l"(p), "r"(bad) : "memory");
}
__device__ __forceinline__ uint32_t or3(uint32_t a, uint32_t b, uint32_t c) {
    uint32_t r;
    asm("lop3.b32 %0, %1, %2, %3, 0xFE;" : "=r"(r) : "r"(a), "r"(b), "r"(c));
    return r;
}
__device__ __forceinline__ bool any_bit0(uint32_t x) {
    uint32_t r;
    asm volatile("{\n.reg .pred p, q;\n.reg .b32 t;\nand.b32 t, %1, 1;\nsetp.ne.u32 p, t, 0;\nvote.sync.any.pred q, p, 0xffffffff;\n"
                 "selp.u32 %0, 1, 0, q;\n}" : "=r"(r) : "r"(x));
    return r;
}
template <int N, int N0, int S0, int S1>
__device__ __forceinline__ void pkt_issue(Pkt (&v)[N], const uint4* p) {
#pragma unroll
    for (int i = 0; i < N; i++) pkt_load(v[i], p + (i / N0) * S1 + (i % N0) * S0);
}
template <int N, int N0, int S0, int S1>
__device__ __forceinline__ void pkt_poll(Pkt (&v)[N], const uint4* p, uint32_t tag) {
    static_assert(N == 8, "");
#pragma unroll 1
    for (int it = 0;; it++) {
        uint32_t b[N];
#pragma unroll
        for (int i = 0; i < N; i++) b[i] = v[i].bad(tag);
        if (!any_bit0(or3(or3(b[0], b[1], b[2]), or3(b[3], b[4], b[5]), or3(b[6], b[7], 0u)))) break;
#pragma unroll
        for (int i = 0; i < N; i++) pkt_reload(v[i], p + (i / N0) * S1 + (i % N0) * S0, b[i]);
        if (it > (1 << 20)) __trap();
    }
}

__device__ __forceinline__ uint32_t now_ns() {
    uint32_t t;
    asm volatile("mov.u32 %0, %%globaltimer_lo;" : "=r"(t));
    return t;
}
__device__ __forceinline__ void wait_until(uint32_t t) {
#pragma unroll 1
    for (int i = 0; (int)(now_ns() - t) < 0 && i < (1 << 16); i++) {}
}

struct Ptrs { const uint8_t* p[2]; };

__global__ void __cluster_dims__(2, 1, 1) __launch_bounds__(288, 1)
gqa_kernel(const __grid_constant__ Ptrs ptrs, __nv_bfloat16* __restrict__ out, uint32_t slot_ns, uint32_t zero,
           const __grid_constant__ CUtensorMap tmK, const __grid_constant__ CUtensorMap tmV,
           const __grid_constant__ CUtensorMap tmX, const __grid_constant__ CUtensorMap tmWq,
           const __grid_constant__ CUtensorMap tmWo) {
    const uint8_t* const wq = pin(ptrs.p[threadIdx.x >> 10]);
    const uint32_t tstart = now_ns();
    asm volatile("prefetch.tensormap [%0];" ::"l"(&tmWq) : "memory");
    asm volatile("prefetch.tensormap [%0];" ::"l"(&tmK) : "memory");
    if (threadIdx.x == 32)
        asm volatile("cp.async.bulk.prefetch.L2.global [%0], %1;" ::"l"(wq + blockIdx.x * PF_BYTES), "r"(PF_BYTES) : "memory");
    extern __shared__ __align__(1024) uint8_t smem_raw[];
    const uint32_t sb = pin((uint32_t)__cvta_generic_to_shared(smem_raw));
    if (threadIdx.x == 0) {
        mbar_init(sb + BAR_W, 1);
        asm volatile("fence.mbarrier_init.release.cluster;" ::: "memory");
        mbar_expect_tx(sb + BAR_W, 65536);
        tma2d(sb + OFF_WQ, &tmWq, blockIdx.x * 32, 0, sb + BAR_W);
        tma2d(sb + OFF_WQ + 16384, &tmWq, blockIdx.x * 32, 256, sb + BAR_W);
        tma3d(sb + OFF_X, &tmX, 0, 0, 0, sb + BAR_W);
    }
    const int warp = __shfl_sync(0xffffffffu, threadIdx.x >> 5, 0), lane = pin(threadIdx.x & 31);
    const int cta = pin(blockIdx.x), rank = cta & 1, bh = cta >> 1;

    if (warp == 8) {
        const int row0 = bh * 2048 + rank * 64;
        uint64_t pol;
        asm volatile("createpolicy.fractional.L2::evict_first.b64 %0, 1.0;" : "=l"(pol));
        auto issue = [&](int n) {
            const bool isv = n >= 2 * NT - KA || (n >= KA && ((n - KA) & 1));
            const int t = n < KA ? n : n >= 2 * NT - KA ? n - NT : isv ? (n - KA) >> 1 : (n + KA) >> 1;
            const int st = n % NST;
            if (isv) tma2d_hint(sb + st * STAGE, &tmV, rank * 64, bh * 2048 + t * 128, sb + BAR_FULL + 8 * st, pol);
            else tma3d_hint(sb + st * STAGE, &tmK, 0, row0 + t * 128, 0, sb + BAR_FULL + 8 * st, pol);
        };
        if (lane == 0) {
            if (sb & 1023) __trap();
#pragma unroll
            for (int i = 0; i < WIN0; i++) mbar_init(sb + BAR_FULL + 8 * i, 1);
            asm volatile("fence.mbarrier_init.release.cluster;" ::: "memory");
#pragma unroll
            for (int n = 0; n < WIN0; n++) {
                mbar_expect_tx(sb + BAR_FULL + 8 * n, STAGE);
                issue(n);
            }
            for (int i = WIN0; i < NST; i++) mbar_init(sb + BAR_FULL + 8 * i, 1);
            for (int i = 0; i < NST; i++) mbar_init(sb + BAR_EMPTY + 8 * i, 4);
            for (int i = 0; i < NP; i++) {
                mbar_init(sb + BAR_PFULL + 8 * i, 4);
                mbar_init(sb + BAR_PFULL + 8 * (NP + i), 1);
                mbar_expect_tx(sb + BAR_PFULL + 8 * (NP + i), 2048 + 64);
                mbar_init(sb + BAR_PEMPTY + 8 * i, 2);
                mbar_init(sb + BAR_PEMPTY + 8 * (NP + i), 2);
            }
            mbar_init(sb + BAR_STAT, 1);
            mbar_init(sb + BAR_F, 1);
            mbar_init(sb + BAR_D, 4);
            mbar_expect_tx(sb + BAR_STAT, 128);
            for (int i = 0; i < 4; i++) {
                mbar_init(sb + BAR_WO + 8 * i, 1);
                mbar_expect_tx(sb + BAR_WO + 8 * i, 8192);
            }
            asm volatile("fence.mbarrier_init.release.cluster;" ::: "memory");
            asm volatile("prefetch.tensormap [%0];" ::"l"(&tmWo) : "memory");
        }
        __syncwarp();
        asm volatile("bar.arrive 0, 288;" ::: "memory");
        asm volatile("barrier.cluster.arrive.relaxed.aligned;" ::: "memory");
        if (lane == 0) {
            auto wait_free = [&](int n) {
                const int st = n % NST, k = n / NST;
                if (st >= NST0) mbar_wait(sb + BAR_EMPTY + 8 * st, k & 1);
                else if (k) mbar_wait(sb + BAR_EMPTY + 8 * st, (k - 1) & 1);
            };
            const uint32_t t3 = tstart + PA_NS;
#pragma unroll
            for (int n = WIN0; n < 2 * NT; n++) {
                wait_free(n);
                mbar_expect_tx(sb + BAR_FULL + 8 * (n % NST), STAGE);
                if (n < WSW || n >= WSW + WIN - WIN0) {
                    const int d = n - (n < WSW ? WIN0 : WIN);
                    mbar_wait(sb + BAR_FULL + 8 * (d % NST), (d / NST) & 1);
                }
                if (n >= WSW) wait_until(t3 + (n - 3) * slot_ns);
                issue(n);
            }
#pragma unroll
            for (int n = 2 * NT; n < 2 * NT + 4; n++) wait_free(n);
#pragma unroll
            for (int g = 0; g < 4; g++) {
                wait_until(t3 + (WO_SLOT + g * WO_STEP) * slot_ns / 100);
                tma2d(sb + OFF_WO + g * 8192, &tmWo, (cta & 15) * 32, (cta >> 4) * 512 + g * 128, sb + BAR_WO + 8 * g);
            }
        }
        return;
    }

    unsigned epoch;
    asm volatile("ld.relaxed.gpu.global.u32 %0, [%1];" : "=r"(epoch) : "l"(&g_scr.ticket) : "memory");
    epoch >>= 7;
    if (cta < 16 && warp >= 4) {
        const int i = threadIdx.x - 128;
        *reinterpret_cast<uint4*>(out + (i >> 2) * 512 + cta * 32 + (i & 3) * 8) = make_uint4(0, 0, 0, 0);
    }
    const int g8 = lane >> 2, quad = lane & 3;
    const int rh = warp >> 2, g = (warp + 2 * rh) & 3;
    const uint4* const oin = pin(&g_scr.o[((cta >> 4) * 4 + g) * 512 + rh * 64 + lane]);
    uint4* const mine = pin(warp < 4 ? &g_scr.q[cta * 128 + warp * 32 + lane]
                                     : &g_scr.o[(((bh & 7) * 4 + (warp & 2) + (lane >> 4)) * 4 + rank * 2 + (warp & 1)) * 128 +
                                                (bh >> 3) * 16 + (lane & 15)]);
    __nv_bfloat16* const optr = pin(out + (rh * 16 + g * 4 + (lane >> 3)) * 512 + (cta & 15) * 32 + (lane & 7) * 4);
    bar_sync(0, 288);

    {
        const int kq = warp & 3, mt = warp >> 2;
        float c[4][4];
#pragma unroll
        for (int j = 0; j < 4; j++) c[j][0] = c[j][1] = c[j][2] = c[j][3] = 0.f;
        const int ar = mt * 16 + (lane & 15);
        const uint32_t abase = sb + OFF_X + kq * 8192 + ar * 128;
        const int br = lane & 15;
        const uint32_t bbase = sb + OFF_WQ + (kq * 128 + br) * 64;
        pkt_store(mine, 0, 0, 0, 0, epoch & 1);
        mbar_wait(sb + BAR_W, 0);
#pragma unroll
        for (int ks = 0; ks < 8; ks++) {
            uint32_t a[4], b0[4], b1[4];
            ldsm4(a, abase + (ks >> 2) * 4096 + ((((ks & 3) * 2 + (lane >> 4)) ^ (ar & 7)) << 4));
            ldsm4t(b0, bbase + ks * 1024 + (((lane >> 4) ^ ((br >> 1) & 3)) << 4));
            ldsm4t(b1, bbase + ks * 1024 + (((2 + (lane >> 4)) ^ ((br >> 1) & 3)) << 4));
            mma(c[0], a, b0[0], b0[1]);
            mma(c[1], a, b0[2], b0[3]);
            mma(c[2], a, b1[0], b1[1]);
            mma(c[3], a, b1[2], b1[3]);
        }
        bar_sync(1, 256);
        asm volatile("barrier.cluster.arrive.relaxed.aligned;" ::: "memory");
        const uint32_t rb = sb + OFF_QRED + (kq * 2 + mt) * 2048 + lane * 16;
        sts128f(rb, c[0][0], c[0][1], c[1][0], c[1][1]);
        sts128f(rb + 512, c[2][0], c[2][1], c[3][0], c[3][1]);
        sts128f(rb + 1024, c[0][2], c[0][3], c[1][2], c[1][3]);
        sts128f(rb + 1536, c[2][2], c[2][3], c[3][2], c[3][3]);
        bar_sync(1, 256);
    }
    const uint32_t tag = pin((epoch + 1) & 1);

    if (warp < 4) {
        {
            const uint32_t rb = sb + OFF_QRED + warp * 1024 + lane * 16;
            float4 s0 = lds128f(rb), s1 = lds128f(rb + 512);
#pragma unroll
            for (int kq = 1; kq < 4; kq++) {
                float4 t0 = lds128f(rb + kq * 4096), t1 = lds128f(rb + kq * 4096 + 512);
                s0.x += t0.x; s0.y += t0.y; s0.z += t0.z; s0.w += t0.w;
                s1.x += t1.x; s1.y += t1.y; s1.z += t1.z; s1.w += t1.w;
            }
            pkt_store(mine, pack_bf16_tagged(s0.x, s0.y, tag), pack_bf16(s0.z, s0.w),
                      pack_bf16_tagged(s1.x, s1.y, tag), pack_bf16(s1.z, s1.w), tag);
            __syncwarp();
            if (lane < NST - NST0) mbar_arrive(sb + BAR_EMPTY + 8 * (NST0 + lane));
        }
        __nanosleep(Q_DELAY_NS);
        uint32_t q[8][4];
        {
            Pkt v[8];
            const uint4* qp = &g_scr.q[(((bh & 7) * 4 + (lane >> 4)) * 4) * 128 + (bh >> 3) * 16 + (lane & 15)];
            pkt_issue<8, 4, 128, 1024>(v, qp);
            pkt_poll<8, 4, 128, 1024>(v, qp, tag);
#pragma unroll
            for (int dq = 0; dq < 4; dq++) {
                const Pkt &a = v[dq], &b = v[4 + dq];
                q[2 * dq][0] = a.w0();     q[2 * dq][1] = b.w0();     q[2 * dq][2] = a.w1();     q[2 * dq][3] = b.w1();
                q[2 * dq + 1][0] = a.w2(); q[2 * dq + 1][1] = b.w2(); q[2 * dq + 1][2] = a.w3(); q[2 * dq + 1][3] = b.w3();
            }
        }
        asm volatile("barrier.cluster.wait.acquire.aligned;" ::: "memory");
        constexpr float C = 0.08838834764831845f * 1.4426950408889634f;
        float mc0 = -INFINITY, mc1 = -INFINITY, l0 = 0.f, l1 = 0.f;
        const int key = warp * 16 + (lane >> 4) * 8 + (lane & 7);
        const uint32_t koff = key * 128;
        const int ksel = (lane >> 3) & 1, kx = lane & 7;
        const uint32_t rp = mapa(sb + OFF_P + NP * 2048 + warp * 512 + lane * 16, rank ^ 1);
        const uint32_t ra = mapa(sb + OFF_ALPHA + NP * 64 + g8 * 4, rank ^ 1), rfull = mapa(sb + BAR_PFULL + 8 * NP, rank ^ 1);
        int st = 0;
        uint32_t par = 0;
#pragma unroll 1
        for (int i = 0; i < NT; i++) {
            const uint32_t kb = sb + st * STAGE + koff;
            float s[2][2][4];
#pragma unroll
            for (int j = 0; j < 4; j++) s[0][0][j] = s[0][1][j] = s[1][0][j] = s[1][1][j] = 0.f;
            mbar_wait(sb + BAR_FULL + 8 * st, par);
#pragma unroll
            for (int ks = 0; ks < 8; ks++) {
                uint32_t b[4];
                ldsm4(b, kb + (ks >> 2) * 8192 + ((((ks & 3) * 2 + ksel) ^ kx) << 4));
                mma(s[ks & 1][0], q[ks], b[0], b[1]);
                mma(s[ks & 1][1], q[ks], b[2], b[3]);
            }
            __syncwarp();
            if (lane == 0) mbar_arrive(sb + BAR_EMPTY + 8 * st);
            st += i < KA ? 1 : 2;
            if (st >= NST) { st -= NST; par ^= 1; }
            float sv[2][4];
#pragma unroll
            for (int j = 0; j < 4; j++) { sv[0][j] = s[0][0][j] + s[1][0][j]; sv[1][j] = s[0][1][j] + s[1][1][j]; }
            float t0 = fmaxf(fmaxf(sv[0][0], sv[0][1]), fmaxf(sv[1][0], sv[1][1]));
            float t1 = fmaxf(fmaxf(sv[0][2], sv[0][3]), fmaxf(sv[1][2], sv[1][3]));
            t0 = fmaxf(t0, __shfl_xor_sync(0xffffffffu, t0, 1));
            t1 = fmaxf(t1, __shfl_xor_sync(0xffffffffu, t1, 1));
            t0 = fmaxf(t0, __shfl_xor_sync(0xffffffffu, t0, 2));
            t1 = fmaxf(t1, __shfl_xor_sync(0xffffffffu, t1, 2));
            const uint32_t wm = sb + OFF_WMAX + (i & 1) * 256 + g8 * 16;
            if (quad == 0) { sts32f(wm + warp * 4, t0); sts32f(wm + 128 + warp * 4, t1); }
            bar_sync(2, 128);
            const float4 w0 = lds128f(wm), w1 = lds128f(wm + 128);
            const float n0 = fmaxf(mc0, fmaxf(fmaxf(w0.x, w0.y), fmaxf(w0.z, w0.w)) * C);
            const float n1 = fmaxf(mc1, fmaxf(fmaxf(w1.x, w1.y), fmaxf(w1.z, w1.w)) * C);
            const float a0 = ex2(mc0 - n0), a1 = ex2(mc1 - n1);
            mc0 = n0; mc1 = n1;
            float p[2][4];
#pragma unroll
            for (int j = 0; j < 2; j++) {
                p[j][0] = ex2(fmaf(sv[j][0], C, -n0)); p[j][1] = ex2(fmaf(sv[j][1], C, -n0));
                p[j][2] = ex2(fmaf(sv[j][2], C, -n1)); p[j][3] = ex2(fmaf(sv[j][3], C, -n1));
            }
            l0 = l0 * a0 + ((p[0][0] + p[0][1]) + (p[1][0] + p[1][1]));
            l1 = l1 * a1 + ((p[0][2] + p[0][3]) + (p[1][2] + p[1][3]));
            const int slot = i % NP;
            if (i >= NP) {
                mbar_wait(sb + BAR_PEMPTY + 8 * slot, (i / NP - 1) & 1);
                mbar_wait(sb + BAR_PEMPTY + 8 * (NP + slot), (i / NP - 1) & 1);
            }
            const uint32_t p0 = pack_bf16(p[0][0], p[0][1]), p1 = pack_bf16(p[0][2], p[0][3]), p2 = pack_bf16(p[1][0], p[1][1]),
                           p3 = pack_bf16(p[1][2], p[1][3]);
            asm volatile("st.async.weak.shared::cluster.mbarrier::complete_tx::bytes.v4.b32 [%0], {%1,%2,%3,%4}, [%5];"
                         ::"r"(rp + slot * 2048), "r"(p1), "r"(p0), "r"(p3), "r"(p2), "r"(rfull + 8 * slot) : "memory");
            sts128(sb + OFF_P + slot * 2048 + warp * 512 + lane * 16, p0, p1, p2, p3);
            if (warp == 0 && quad == 0) {
                asm volatile("st.async.weak.shared::cluster.mbarrier::complete_tx::bytes.f32 [%0], %1, [%2];"
                             ::"r"(ra + slot * 64), "f"(a1), "r"(rfull + 8 * slot) : "memory");
                asm volatile("st.async.weak.shared::cluster.mbarrier::complete_tx::bytes.f32 [%0], %1, [%2];"
                             ::"r"(ra + slot * 64 + 32), "f"(a0), "r"(rfull + 8 * slot) : "memory");
                sts32f(sb + OFF_ALPHA + slot * 64 + g8 * 4, a0);
                sts32f(sb + OFF_ALPHA + slot * 64 + 32 + g8 * 4, a1);
            }
            __syncwarp();
            if (lane == 0) mbar_arrive(sb + BAR_PFULL + 8 * slot);
        }
        l0 += __shfl_xor_sync(0xffffffffu, l0, 1);
        l1 += __shfl_xor_sync(0xffffffffu, l1, 1);
        l0 += __shfl_xor_sync(0xffffffffu, l0, 2);
        l1 += __shfl_xor_sync(0xffffffffu, l1, 2);
        if (quad == 0) {
            sts32f(sb + OFF_LSUM + g8 * 16 + warp * 4, l0);
            sts32f(sb + OFF_LSUM + 128 + g8 * 16 + warp * 4, l1);
            if (warp == 0) { sts32f(sb + OFF_MROW + g8 * 4, mc0); sts32f(sb + OFF_MROW + 32 + g8 * 4, mc1); }
        }
        bar_sync(2, 128);
        if (warp == 0) {
            if (lane < 16) {
                const float4 lv = lds128f(sb + OFF_LSUM + lane * 16);
                const float l = (lv.x + lv.y) + (lv.z + lv.w), m = lds32f(sb + OFF_MROW + lane * 4);
                asm volatile("st.async.weak.shared::cluster.mbarrier::complete_tx::bytes.v2.f32 [%0], {%1,%2}, [%3];"
                             ::"r"(mapa(sb + OFF_STAT + lane * 8, rank ^ 1)), "f"(m), "f"(l), "r"(mapa(sb + BAR_STAT, rank ^ 1)) : "memory");
                mbar_wait(sb + BAR_STAT, 0);
                const float pm = lds32f(sb + OFF_STAT + lane * 8), pl = lds32f(sb + OFF_STAT + lane * 8 + 4);
                const float mm = fmaxf(m, pm);
                const float e = ex2(m - mm), pe = ex2(pm - mm);
                const float inv = __fdividef(1.f, rank ? pl * pe + l * e : l * e + pl * pe);
                sts32f(sb + OFF_F + lane * 4, e * inv);
                sts32f(sb + OFF_F + 64 + (lane ^ 8) * 4, pe * inv);
            }
            __syncwarp();
            if (lane == 0) mbar_arrive(sb + BAR_F);
        }
        mbar_wait(sb + BAR_D, 0);
    } else {
        const int w = warp - 4;
        asm volatile("barrier.cluster.wait.acquire.aligned;" ::: "memory");
        if (threadIdx.x == 128) {
            asm volatile("red.relaxed.gpu.global.add.u32 [%0], 1;" ::"l"(&g_scr.ticket) : "memory");
            if (cta < 16) asm volatile("st.release.gpu.global.u32 [%0], %1;" ::"l"(&g_scr.zeroed[cta * 32]), "r"(epoch + 1) : "memory");
            unsigned z;
#pragma unroll 1
            for (int it = 0;; it++) {
                asm volatile("ld.acquire.gpu.global.u32 %0, [%1];" : "=r"(z) : "l"(&g_scr.zeroed[(cta & 15) * 32]) : "memory");
                if (z == epoch + 1) break;
                if (it > (1 << 20)) __trap();
                __nanosleep(200);
            }
        }
        __syncwarp();
        const int src = w >> 1, ds = w & 1;
        const uint32_t pbase = pin(sb + OFF_P + src * NP * 2048 + lane * 16), abase = pin(sb + OFF_ALPHA + src * NP * 64 + g8 * 4);
        const uint32_t pfull = pin(sb + BAR_PFULL + src * NP * 8);
        const uint32_t pempty = src ? mapa(sb + BAR_PEMPTY + 8 * NP, rank ^ 1) : mapa(sb + BAR_PEMPTY, rank);
        float o[4][4], t[2][4][4];
#pragma unroll
        for (int j = 0; j < 16; j++) (&o[0][0])[j] = (&t[0][0][0])[j] = (&t[1][0][0])[j] = 0.f;
        const uint32_t voff = ((rank ^ src) * 64 + (lane & 15)) * 128;
        const int vc = ds * 4 + (lane >> 4), vx = lane & 7;
        const uint32_t v0 = pin(sb + voff + ((vc ^ vx) << 4)), v1 = pin(sb + voff + (((vc + 2) ^ vx) << 4));
        uint32_t p[4][4], b0[4][4], b1[4][4];
        float a0 = 0.f, a1 = 0.f;
        auto load_v = [&](int st) {
#pragma unroll
            for (int j = 0; j < 4; j++) {
                ldsm4t(b0[j], v0 + st * STAGE + j * 2048);
                ldsm4t(b1[j], v1 + st * STAGE + j * 2048);
            }
        };
        auto next_p = [&](int i) {
            const int slot = i % NP;
            mbar_wait(pfull + 8 * slot, (i / NP) & 1);
#pragma unroll
            for (int j = 0; j < 4; j++) lds128(p[j], pbase + slot * 2048 + j * 512);
            const float n0 = lds32f(abase + slot * 64), n1 = lds32f(abase + slot * 64 + 32);
            __syncwarp();
            if (lane == 0 && i < NT - NP) {
                if (w == 2) mbar_expect_tx(pfull + 8 * slot, 2048 + 64);
                asm volatile("mbarrier.arrive.relaxed.cluster.shared::cluster.b64 _, [%0];"
                             ::"r"(pempty + 8 * slot + ((p[3][3] | __float_as_uint(n1)) & zero)) : "memory");
            }
#pragma unroll
            for (int j = 0; j < 4; j++) {
                o[j][0] = fmaf(o[j][0], a0, t[0][j][0] + t[1][j][0]); o[j][1] = fmaf(o[j][1], a0, t[0][j][1] + t[1][j][1]);
                o[j][2] = fmaf(o[j][2], a1, t[0][j][2] + t[1][j][2]); o[j][3] = fmaf(o[j][3], a1, t[0][j][3] + t[1][j][3]);
            }
            a0 = n0; a1 = n1;
        };
        auto pv = [&]() {
#pragma unroll
            for (int j = 0; j < 16; j++) (&t[0][0][0])[j] = (&t[1][0][0])[j] = 0.f;
#pragma unroll
            for (int j = 0; j < 4; j++) {
                mma(t[j & 1][0], p[j], b0[j][0], b0[j][1]);
                mma(t[j & 1][1], p[j], b0[j][2], b0[j][3]);
                mma(t[j & 1][2], p[j], b1[j][0], b1[j][1]);
                mma(t[j & 1][3], p[j], b1[j][2], b1[j][3]);
            }
        };
        int st = KA + 1;
        uint32_t par = 0;
#pragma unroll 1
        for (int i = 0; i < NT - 1; i++) {
            mbar_wait(sb + BAR_FULL + 8 * st, par);
            load_v(st);
            next_p(i);
            pv();
            __syncwarp();
            if (lane == 0) mbar_arrive(sb + BAR_EMPTY + 8 * st);
            st += i < NT - KA - 1 ? 2 : 1;
            if (st >= NST) { st -= NST; par ^= 1; }
        }
        constexpr int LST = (2 * NT - 1) % NST, LPAR = ((2 * NT - 1) / NST) & 1;
        const bool landed = mbar_test(sb + BAR_FULL + 8 * LST, LPAR);
        if (landed) load_v(LST);
        next_p(NT - 1);
        mbar_wait(sb + BAR_F, 0);
        const float f0 = lds32f(sb + OFF_F + src * 64 + g8 * 4), f1 = lds32f(sb + OFF_F + src * 64 + 32 + g8 * 4);
        a0 *= f0; a1 *= f1;
#pragma unroll
        for (int j = 0; j < 4; j++) {
            o[j][0] *= a0; o[j][1] *= a0; o[j][2] *= a1; o[j][3] *= a1;
            asm volatile("" : "+f"(o[j][0]), "+f"(o[j][1]), "+f"(o[j][2]), "+f"(o[j][3]));
        }
        if (!landed) {
            mbar_wait(sb + BAR_FULL + 8 * LST, LPAR);
            load_v(LST);
        }
        pv();
#pragma unroll
        for (int j = 0; j < 4; j++) {
            o[j][0] = fmaf(t[0][j][0] + t[1][j][0], f0, o[j][0]); o[j][1] = fmaf(t[0][j][1] + t[1][j][1], f0, o[j][1]);
            o[j][2] = fmaf(t[0][j][2] + t[1][j][2], f1, o[j][2]); o[j][3] = fmaf(t[0][j][3] + t[1][j][3], f1, o[j][3]);
        }
        {
            const uint32_t ours = sb + OFF_MERGE + w * 1024 + lane * 16, theirs = sb + OFF_MERGE + (w ^ 2) * 1024 + lane * 16;
            sts128f(theirs, o[0][2], o[0][3], o[1][2], o[1][3]);
            sts128f(theirs + 512, o[2][2], o[2][3], o[3][2], o[3][3]);
            bar_sync(5 + ds, 64);
            const float4 r0 = lds128f(ours), r1 = lds128f(ours + 512);
            pkt_store(mine, pack_bf16(o[0][0] + r0.x, o[0][1] + r0.y), pack_bf16(o[1][0] + r0.z, o[1][1] + r0.w),
                      pack_bf16(o[2][0] + r1.x, o[2][1] + r1.y), pack_bf16(o[3][0] + r1.z, o[3][1] + r1.w), tag);
        }
        if (lane == 0) mbar_arrive(sb + BAR_D);
    }

    {
        uint32_t a[8][2][4];
        const int kr = (lane >> 4) * 8 + (lane & 7);
        const int wc = (lane >> 3) & 1, wx = (kr >> 1) & 3;
        const uint32_t wb0 = pin(sb + OFF_WO + (g * 128 + kr) * 64 + ((wc ^ wx) << 4));
        const uint32_t wb1 = pin(sb + OFF_WO + (g * 128 + kr) * 64 + (((wc + 2) ^ wx) << 4));
        const uint32_t rw = pin(sb + OFF_PRED + (rh * 4 + g) * 2304 + quad * 288 + g8 * 4);
        const uint32_t rr = pin(sb + OFF_PRED + rh * 4 * 2304 + (g * 4 + (lane >> 3)) * 144 + (lane & 7) * 16);
        const uint32_t wobar = sb + BAR_WO + 8 * g;
        constexpr uint32_t wopar = 0;
        auto wo_within = [&](uint32_t clks) {
            uint32_t c0, c1;
            bool in;
            asm volatile("mov.u32 %0, %%clock;" : "=r"(c0));
            do {
                in = mbar_test(wobar, wopar);
                asm volatile("mov.u32 %0, %%clock;" : "=r"(c1));
            } while (!in && c1 - c0 < clks);
            return in;
        };
        Pkt v[8];
        const bool in0 = wo_within(O_DELAY);
        pkt_issue<8, 4, 128, 32>(v, oin);
        if (!in0) {
#pragma unroll 1
            for (int it = 0; !wo_within(O_PERIOD); it++) {
                uint32_t b[8];
#pragma unroll
                for (int i = 0; i < 8; i++) b[i] = v[i].bad(tag);
                if (it > (1 << 16)) __trap();
#pragma unroll
                for (int i = 0; i < 8; i++) pkt_reload(v[i], oin + (i >> 2) * 32 + (i & 3) * 128, b[i]);
            }
        }
#pragma unroll
        for (int ks = 0; ks < 8; ks++) {
            ldsm4t(a[ks][0], wb0 + ks * 1024);
            ldsm4t(a[ks][1], wb1 + ks * 1024);
        }
        pkt_poll<8, 4, 128, 32>(v, oin, tag | (a[7][1][3] & zero));
        float c[2][2][4];
#pragma unroll
        for (int j = 0; j < 16; j++) (&c[0][0][0])[j] = 0.f;
#pragma unroll
        for (int ks = 0; ks < 8; ks++)
#pragma unroll
            for (int t = 0; t < 2; t++) {
                const Pkt& pk = v[t * 4 + (ks >> 1)];
                mma(c[t][0], a[ks][0], ks & 1 ? pk.w2() : pk.w0(), ks & 1 ? pk.w3() : pk.w1());
                mma(c[t][1], a[ks][1], ks & 1 ? pk.w2() : pk.w0(), ks & 1 ? pk.w3() : pk.w1());
            }
#pragma unroll
        for (int t = 0; t < 2; t++)
#pragma unroll
            for (int mt = 0; mt < 2; mt++)
#pragma unroll
                for (int e = 0; e < 4; e++) sts32f(rw + (t * 8 + (e & 1)) * 144 + (mt * 16 + (e >> 1) * 8) * 4, c[t][mt][e]);
        bar_sync(3 + rh, 128);
        const float4 s0 = lds128f(rr), s1 = lds128f(rr + 2304), s2 = lds128f(rr + 2 * 2304), s3 = lds128f(rr + 3 * 2304);
        asm volatile("red.relaxed.gpu.global.add.noftz.v2.bf16x2 [%0], {%1, %2};"
                     ::"l"(optr), "r"(pack_bf16((s0.x + s1.x) + (s2.x + s3.x), (s0.y + s1.y) + (s2.y + s3.y))),
                       "r"(pack_bf16((s0.z + s1.z) + (s2.z + s3.z), (s0.w + s1.w) + (s2.w + s3.w))) : "memory");
    }

}

__global__ void fb_proj(const __nv_bfloat16* a_bf, const float* a_f, const __nv_bfloat16* w, int K, int N, float* o_f,
                        __nv_bfloat16* o_bf) {
    const int c = blockIdx.x * blockDim.x + threadIdx.x, r = blockIdx.y;
    float s = 0.f;
    for (int k = 0; k < K; k++) s += (a_bf ? __bfloat162float(a_bf[r * K + k]) : a_f[r * K + k]) * __bfloat162float(w[k * N + c]);
    if (o_bf) o_bf[r * N + c] = __float2bfloat16(s);
    else o_f[r * N + c] = __bfloat162float(__float2bfloat16(s));
}
__global__ void fb_attn(const __nv_bfloat16* kc, const __nv_bfloat16* vc) {
    __shared__ float sc[2048], red[128];
    const int r = blockIdx.x, hq = blockIdx.y, t = threadIdx.x;
    const size_t base = (size_t)((r >> 2) * 8 + (hq >> 2)) * 2048 * 128;
    float m = -INFINITY, l = 0.f, acc = 0.f;
    for (int j = t; j < 2048; j += 128) {
        float s = 0.f;
        for (int d = 0; d < 128; d++) s += g_scr.fq[r * 4096 + hq * 128 + d] * __bfloat162float(kc[base + j * 128 + d]);
        sc[j] = s * 0.08838834764831845f;
        m = fmaxf(m, sc[j]);
    }
    red[t] = m;
    __syncthreads();
    for (int i = 0; i < 128; i++) m = fmaxf(m, red[i]);
    for (int j = t; j < 2048; j += 128) sc[j] = __expf(sc[j] - m);
    __syncthreads();
    for (int j = 0; j < 2048; j++) {
        l += sc[j];
        acc += sc[j] * __bfloat162float(vc[base + j * 128 + t]);
    }
    g_scr.fo[r * 4096 + hq * 128 + t] = __bfloat162float(__float2bfloat16(acc / l));
}

typedef CUresult (*EncodeFn)(CUtensorMap*, CUtensorMapDataType, cuuint32_t, void*, const cuuint64_t*, const cuuint64_t*,
                             const cuuint32_t*, const cuuint32_t*, CUtensorMapInterleave, CUtensorMapSwizzle,
                             CUtensorMapL2promotion, CUtensorMapFloatOOBfill);

static void encode(EncodeFn fn, CUtensorMap* m, void* p, int rank, const cuuint64_t* dims, const cuuint64_t* strides,
                   const cuuint32_t* box, CUtensorMapSwizzle sw) {
    const cuuint32_t es[3] = {1, 1, 1};
    fn(m, CU_TENSOR_MAP_DATA_TYPE_BFLOAT16, rank, p, dims, strides, box, es, CU_TENSOR_MAP_INTERLEAVE_NONE, sw,
       CU_TENSOR_MAP_L2_PROMOTION_L2_256B, CU_TENSOR_MAP_FLOAT_OOB_FILL_NONE);
}

}

extern "C" void kernel_launch(void* const* d_in, const int* in_sizes, int n_in, void* d_out, int out_size) {
    using namespace gqa;
    static EncodeFn fn = nullptr;
    static uint32_t slot_ns = SLOT_NS;
    static bool fits = false;
    if (!fn) {
        int dev = 0, khz = 0, bits = 0;
        cudaGetDevice(&dev);
        cudaDeviceGetAttribute(&khz, cudaDevAttrMemoryClockRate, dev);
        cudaDeviceGetAttribute(&bits, cudaDevAttrGlobalMemoryBusWidth, dev);
        if (khz > 0 && bits > 0) slot_ns = (uint32_t)((double)NCTA * STAGE / (0.955 * 2.0 * khz * 1e-6 * (bits / 8)));
        void* p = nullptr;
        cudaDriverEntryPointQueryResult qr;
        cudaGetDriverEntryPoint("cuTensorMapEncodeTiled", &p, cudaEnableDefault, &qr);
        fn = (EncodeFn)p;
        cudaFuncSetAttribute(gqa_kernel, cudaFuncAttributeMaxDynamicSharedMemorySize, SMEM_BYTES);
        cudaLaunchConfig_t cfg = {};
        cfg.gridDim = dim3(NCTA);
        cfg.blockDim = dim3(288);
        cfg.dynamicSmemBytes = SMEM_BYTES;
        int clusters = 0;
        fits = cudaOccupancyMaxActiveClusters(&clusters, gqa_kernel, &cfg) == cudaSuccess && clusters >= NCTA / 2;
    }
    if (!fits) {
        Scratch* scr = nullptr;
        cudaGetSymbolAddress((void**)&scr, g_scr);
        float *fq = scr->fq, *fo = scr->fo;
        fb_proj<<<dim3(16, 32), 256, 0, cudaStreamPerThread>>>((const __nv_bfloat16*)d_in[0], nullptr, (const __nv_bfloat16*)d_in[3], 512,
                                                               4096, fq, nullptr);
        fb_attn<<<dim3(32, 32), 128, 0, cudaStreamPerThread>>>((const __nv_bfloat16*)d_in[1], (const __nv_bfloat16*)d_in[2]);
        fb_proj<<<dim3(2, 32), 256, 0, cudaStreamPerThread>>>(nullptr, fo, (const __nv_bfloat16*)d_in[4], 4096, 512, nullptr,
                                                              (__nv_bfloat16*)d_out);
        return;
    }
    CUtensorMap tmK, tmV, tmX, tmWq, tmWo;
    {
        const cuuint64_t dims[3] = {64, 8 * 8 * 2048, 2}, str[2] = {256, 128};
        const cuuint32_t box[3] = {64, 64, 2};
        encode(fn, &tmK, d_in[1], 3, dims, str, box, CU_TENSOR_MAP_SWIZZLE_128B);
        const cuuint64_t dv[2] = {128, 8 * 8 * 2048}, sv[1] = {256};
        const cuuint32_t bv[2] = {64, 128};
        encode(fn, &tmV, d_in[2], 2, dv, sv, bv, CU_TENSOR_MAP_SWIZZLE_128B);
    }
    {
        const cuuint64_t dims[3] = {64, 32, 8}, str[2] = {1024, 128};
        const cuuint32_t box[3] = {64, 32, 8};
        encode(fn, &tmX, d_in[0], 3, dims, str, box, CU_TENSOR_MAP_SWIZZLE_128B);
    }
    {
        const cuuint64_t dq[2] = {4096, 512}, sq[1] = {8192}, dw[2] = {512, 4096}, sw[1] = {1024};
        const cuuint32_t box[2] = {32, 256};
        encode(fn, &tmWq, d_in[3], 2, dq, sq, box, CU_TENSOR_MAP_SWIZZLE_64B);
        const cuuint32_t boxo[2] = {32, 128};
        encode(fn, &tmWo, d_in[4], 2, dw, sw, boxo, CU_TENSOR_MAP_SWIZZLE_64B);
    }
    gqa_kernel<<<NCTA, 288, SMEM_BYTES, cudaStreamPerThread>>>(Ptrs{{(const uint8_t*)d_in[3], nullptr}}, (__nv_bfloat16*)d_out, slot_ns, 0u, tmK, tmV, tmX,
                                                               tmWq, tmWo);
}
```

```cpp
#include <cuda_runtime.h>
#include <cuda_bf16.h>
#include <cuda.h>
#include <stdint.h>

namespace gqa {

constexpr int PA_NS = 2780;
constexpr int SLOT_NS = 655;
constexpr int WO_SLOT = 2880;
constexpr int WO_STEP = 65;
constexpr int Q_DELAY_NS = 1200;
constexpr int O_DELAY = 1000;
constexpr int O_PERIOD = 350;
constexpr int PF_BYTES = 8192;

constexpr int NCTA = 128;
constexpr int NT = 16;
constexpr int NST = 13;
constexpr int NST0 = 10;
constexpr int WIN0 = 3;
constexpr int WIN = 8;
constexpr int WSW = 8;
constexpr int KA = 2;
constexpr int NP = 4;
constexpr int STAGE = 16384;

constexpr int OFF_WQ = NST0 * STAGE;
constexpr int OFF_X = OFF_WQ + 32768;
constexpr int OFF_QRED = OFF_X;
constexpr int OFF_WO = ((2 * NT) % NST) * STAGE;
constexpr int OFF_P = NST * STAGE;
constexpr int OFF_MERGE = (((2 * NT) % NST) + 3) * STAGE + 8192;
constexpr int OFF_ALPHA = (NST + 1) * STAGE + 512;
constexpr int OFF_WMAX = OFF_ALPHA + 2 * NP * 64;
constexpr int OFF_LSUM = OFF_WMAX + 512;
constexpr int OFF_MROW = OFF_LSUM + 256;
constexpr int OFF_STAT = OFF_MROW + 64;
constexpr int OFF_F = OFF_STAT + 128;
constexpr int OFF_PRED = (((2 * NT) % NST) + 2) * STAGE;
constexpr int OFF_BAR = (NST + 1) * STAGE;
constexpr int BAR_FULL = OFF_BAR;
constexpr int BAR_EMPTY = BAR_FULL + 8 * NST;
constexpr int BAR_PFULL = BAR_EMPTY + 8 * NST;
constexpr int BAR_PEMPTY = BAR_PFULL + 16 * NP;
constexpr int BAR_W = BAR_PEMPTY + 16 * NP;
constexpr int BAR_STAT = BAR_W + 8;
constexpr int BAR_F = BAR_STAT + 8;
constexpr int BAR_D = BAR_F + 8;
constexpr int BAR_WO = BAR_D + 8;
constexpr int SMEM_BYTES = OFF_F + 128;
static_assert(2 * NP * 2048 <= STAGE, "P slots overflow");
static_assert(BAR_WO + 32 <= OFF_ALPHA, "barriers overflow");
static_assert((2 * NT) % NST + 3 < NST, "wo / partial slots must not wrap");
static_assert(SMEM_BYTES <= 232448, "too much shared memory");

struct __align__(1024) Scratch {
    uint4 q[32 * 4 * 8 * 16];
    uint4 o[32 * 4 * 8 * 16];
    unsigned ticket;
    unsigned pad[31];
    unsigned zeroed[16 * 32];
    float fq[32 * 4096], fo[32 * 4096];
};
__device__ Scratch g_scr;

__device__ __forceinline__ void mbar_init(uint32_t bar, uint32_t cnt) {
    asm volatile("mbarrier.init.shared::cta.b64 [%0], %1;" ::"r"(bar), "r"(cnt) : "memory");
}
__device__ __forceinline__ void mbar_expect_tx(uint32_t bar, uint32_t bytes) {
    asm volatile("mbarrier.arrive.expect_tx.shared::cta.b64 _, [%0], %1;" ::"r"(bar), "r"(bytes) : "memory");
}
__device__ __forceinline__ void mbar_arrive(uint32_t bar) {
    asm volatile("mbarrier.arrive.shared::cta.b64 _, [%0];" ::"r"(bar) : "memory");
}
__device__ __forceinline__ bool mbar_try(uint32_t bar, uint32_t parity) {
    uint32_t ok;
    asm volatile("{\n.reg .pred p;\nmbarrier.try_wait.parity.shared::cta.b64 p, [%1], %2;\nselp.u32 %0, 1, 0, p;\n}"
                 : "=r"(ok) : "r"(bar), "r"(parity) : "memory");
    return ok;
}
__device__ __forceinline__ bool mbar_test(uint32_t bar, uint32_t parity) {
    uint32_t ok;
    asm volatile("{\n.reg .pred p;\nmbarrier.test_wait.parity.shared::cta.b64 p, [%1], %2;\nselp.u32 %0, 1, 0, p;\n}"
                 : "=r"(ok) : "r"(bar), "r"(parity) : "memory");
    return ok;
}
__device__ __forceinline__ void mbar_wait(uint32_t bar, uint32_t parity) {
#pragma unroll 1
    for (int i = 0; !mbar_try(bar, parity); i++)
        if (i > (1 << 20)) __trap();
}
__device__ __forceinline__ void tma2d(uint32_t dst, const CUtensorMap* m, int c0, int c1, uint32_t bar) {
    asm volatile("cp.async.bulk.tensor.2d.shared::cluster.global.mbarrier::complete_tx::bytes [%0], [%1, {%3, %4}], [%2];"
                 ::"r"(dst), "l"(m), "r"(bar), "r"(c0), "r"(c1) : "memory");
}
__device__ __forceinline__ void tma3d(uint32_t dst, const CUtensorMap* m, int c0, int c1, int c2, uint32_t bar) {
    asm volatile("cp.async.bulk.tensor.3d.shared::cluster.global.mbarrier::complete_tx::bytes [%0], [%1, {%3, %4, %5}], [%2];"
                 ::"r"(dst), "l"(m), "r"(bar), "r"(c0), "r"(c1), "r"(c2) : "memory");
}
__device__ __forceinline__ void tma2d_hint(uint32_t dst, const CUtensorMap* m, int c0, int c1, uint32_t bar, uint64_t pol) {
    asm volatile("cp.async.bulk.tensor.2d.shared::cluster.global.mbarrier::complete_tx::bytes.L2::cache_hint [%0], [%1, {%3, %4}], [%2], %5;"
                 ::"r"(dst), "l"(m), "r"(bar), "r"(c0), "r"(c1), "l"(pol) : "memory");
}
__device__ __forceinline__ uint32_t mapa(uint32_t addr, uint32_t cta_rank) {
    uint32_t r;
    asm("mapa.shared::cluster.u32 %0, %1, %2;" : "=r"(r) : "r"(addr), "r"(cta_rank));
    return r;
}
__device__ __forceinline__ void tma3d_hint(uint32_t dst, const CUtensorMap* m, int c0, int c1, int c2, uint32_t bar, uint64_t pol) {
    asm volatile("cp.async.bulk.tensor.3d.shared::cluster.global.mbarrier::complete_tx::bytes.L2::cache_hint [%0], [%1, {%3, %4, %5}], [%2], %6;"
                 ::"r"(dst), "l"(m), "r"(bar), "r"(c0), "r"(c1), "r"(c2), "l"(pol) : "memory");
}
__device__ __forceinline__ void ldsm4(uint32_t (&r)[4], uint32_t addr) {
    asm volatile("ldmatrix.sync.aligned.m8n8.x4.shared.b16 {%0,%1,%2,%3}, [%4];"
                 : "=r"(r[0]), "=r"(r[1]), "=r"(r[2]), "=r"(r[3]) : "r"(addr) : "memory");
}
__device__ __forceinline__ void ldsm4t(uint32_t (&r)[4], uint32_t addr) {
    asm volatile("ldmatrix.sync.aligned.m8n8.x4.trans.shared.b16 {%0,%1,%2,%3}, [%4];"
                 : "=r"(r[0]), "=r"(r[1]), "=r"(r[2]), "=r"(r[3]) : "r"(addr) : "memory");
}
__device__ __forceinline__ void mma(float (&c)[4], const uint32_t (&a)[4], uint32_t b0, uint32_t b1) {
    asm volatile("mma.sync.aligned.m16n8k16.row.col.f32.bf16.bf16.f32 {%0,%1,%2,%3}, {%4,%5,%6,%7}, {%8,%9}, {%0,%1,%2,%3};"
                 : "+f"(c[0]), "+f"(c[1]), "+f"(c[2]), "+f"(c[3])
                 : "r"(a[0]), "r"(a[1]), "r"(a[2]), "r"(a[3]), "r"(b0), "r"(b1));
}
__device__ __forceinline__ uint32_t pack_bf16(float lo, float hi) {
    uint32_t r;
    asm("cvt.rn.bf16x2.f32 %0, %1, %2;" : "=r"(r) : "f"(hi), "f"(lo));
    return r;
}
__device__ __forceinline__ float ex2(float x) {
    float y;
    asm("ex2.approx.ftz.f32 %0, %1;" : "=f"(y) : "f"(x));
    return y;
}
__device__ __forceinline__ void sts128(uint32_t addr, uint32_t a, uint32_t b, uint32_t c, uint32_t d) {
    asm volatile("st.shared.v4.b32 [%0], {%1,%2,%3,%4};" ::"r"(addr), "r"(a), "r"(b), "r"(c), "r"(d) : "memory");
}
__device__ __forceinline__ void sts128f(uint32_t addr, float a, float b, float c, float d) {
    asm volatile("st.shared.v4.f32 [%0], {%1,%2,%3,%4};" ::"r"(addr), "f"(a), "f"(b), "f"(c), "f"(d) : "memory");
}
__device__ __forceinline__ void sts32f(uint32_t addr, float a) {
    asm volatile("st.shared.f32 [%0], %1;" ::"r"(addr), "f"(a) : "memory");
}
__device__ __forceinline__ void lds128(uint32_t (&r)[4], uint32_t addr) {
    asm volatile("ld.shared.v4.b32 {%0,%1,%2,%3}, [%4];" : "=r"(r[0]), "=r"(r[1]), "=r"(r[2]), "=r"(r[3]) : "r"(addr) : "memory");
}
__device__ __forceinline__ float4 lds128f(uint32_t addr) {
    float4 v;
    asm volatile("ld.shared.v4.f32 {%0,%1,%2,%3}, [%4];" : "=f"(v.x), "=f"(v.y), "=f"(v.z), "=f"(v.w) : "r"(addr) : "memory");
    return v;
}
__device__ __forceinline__ float lds32f(uint32_t addr) {
    float v;
    asm volatile("ld.shared.f32 %0, [%1];" : "=f"(v) : "r"(addr) : "memory");
    return v;
}
__device__ __forceinline__ void bar_sync(int id, int n) { asm volatile("bar.sync %0, %1;" ::"r"(id), "r"(n) : "memory"); }
template <typename T> __device__ __forceinline__ T* pin(T* p) { asm volatile("" : "+l"(p)); return p; }
__device__ __forceinline__ uint32_t pin(uint32_t v) { asm volatile("" : "+r"(v)); return v; }

struct Pkt {
    uint64_t lo, hi;
    __device__ __forceinline__ uint32_t w0() const { return (uint32_t)lo; }
    __device__ __forceinline__ uint32_t w1() const { return (uint32_t)(lo >> 32); }
    __device__ __forceinline__ uint32_t w2() const { return (uint32_t)hi; }
    __device__ __forceinline__ uint32_t w3() const { return (uint32_t)(hi >> 32); }
    __device__ __forceinline__ uint32_t bad(uint32_t tag) const {
        uint32_t r;
        asm("lop3.b32 %0, %1, %2, %3, 0x7E;" : "=r"(r) : "r"(w0()), "r"(w2()), "r"(tag));
        return r;
    }
};
__device__ __forceinline__ void pkt_store(uint4* p, uint32_t a, uint32_t b, uint32_t c, uint32_t d, uint32_t tag) {
    a = (a & ~1u) | tag;
    c = (c & ~1u) | tag;
    asm volatile("{\n.reg .b64 lo, hi;\nmov.b64 lo, {%1,%2};\nmov.b64 hi, {%3,%4};\n"
                 "st.relaxed.gpu.global.v2.b64 [%0], {lo, hi};\n}" ::"l"(p), "r"(a), "r"(b), "r"(c), "r"(d) : "memory");
}
__device__ __forceinline__ uint32_t pack_bf16_tagged(float lo, float hi, uint32_t tag) {
    uint32_t r = pack_bf16(lo, hi);
    if ((r ^ tag) & 1u) {
        const uint32_t mag = r & 0x7fffu;
        const bool up = mag == 0 || (fabsf(lo) > __uint_as_float(mag << 16) && mag < 0x7f7fu);
        r += up ? 1u : 0xffffffffu;
    }
    return r;
}
__device__ __forceinline__ void pkt_load(Pkt& v, const uint4* p) {
    asm volatile("ld.relaxed.gpu.global.v2.b64 {%0, %1}, [%2];" : "=l"(v.lo), "=l"(v.hi) : "l"(p) : "memory");
}
__device__ __forceinline__ void pkt_reload(Pkt& v, const uint4* p, uint32_t bad) {
    asm volatile("{\n.reg .pred p;\n.reg .b32 t;\nand.b32 t, %3, 1;\nsetp.ne.u32 p, t, 0;\n"
                 "@p ld.relaxed.gpu.global.v2.b64 {%0, %1}, [%2];\n}"
                 : "+l"(v.lo), "+l"(v.hi) : "l"(p), "r"(bad) : "memory");
}
__device__ __forceinline__ uint32_t or3(uint32_t a, uint32_t b, uint32_t c) {
    uint32_t r;
    asm("lop3.b32 %0, %1, %2, %3, 0xFE;" : "=r"(r) : "r"(a), "r"(b), "r"(c));
    return r;
}
__device__ __forceinline__ bool any_bit0(uint32_t x) {
    uint32_t r;
    asm volatile("{\n.reg .pred p, q;\n.reg .b32 t;\nand.b32 t, %1, 1;\nsetp.ne.u32 p, t, 0;\nvote.sync.any.pred q, p, 0xffffffff;\n"
                 "selp.u32 %0, 1, 0, q;\n}" : "=r"(r) : "r"(x));
    return r;
}
template <int N, int N0, int S0, int S1>
__device__ __forceinline__ void pkt_issue(Pkt (&v)[N], const uint4* p) {
#pragma unroll
    for (int i = 0; i < N; i++) pkt_load(v[i], p + (i / N0) * S1 + (i % N0) * S0);
}
template <int N, int N0, int S0, int S1>
__device__ __forceinline__ void pkt_poll(Pkt (&v)[N], const uint4* p, uint32_t tag) {
    static_assert(N == 8, "");
#pragma unroll 1
    for (int it = 0;; it++) {
        uint32_t b[N];
#pragma unroll
        for (int i = 0; i < N; i++) b[i] = v[i].bad(tag);
        if (!any_bit0(or3(or3(b[0], b[1], b[2]), or3(b[3], b[4], b[5]), or3(b[6], b[7], 0u)))) break;
#pragma unroll
        for (int i = 0; i < N; i++) pkt_reload(v[i], p + (i / N0) * S1 + (i % N0) * S0, b[i]);
        if (it > (1 << 20)) __trap();
    }
}

__device__ __forceinline__ uint32_t now_ns() {
    uint32_t t;
    asm volatile("mov.u32 %0, %%globaltimer_lo;" : "=r"(t));
    return t;
}
__device__ __forceinline__ void wait_until(uint32_t t) {
#pragma unroll 1
    for (int i = 0; (int)(now_ns() - t) < 0 && i < (1 << 16); i++) {}
}

struct Ptrs { const uint8_t* p[2]; };

__global__ void __cluster_dims__(2, 1, 1) __launch_bounds__(288, 1)
gqa_kernel(const __grid_constant__ Ptrs ptrs, __nv_bfloat16* __restrict__ out, uint32_t slot_ns, uint32_t zero,
           const __grid_constant__ CUtensorMap tmK, const __grid_constant__ CUtensorMap tmV,
           const __grid_constant__ CUtensorMap tmX, const __grid_constant__ CUtensorMap tmWq,
           const __grid_constant__ CUtensorMap tmWo) {
    const uint8_t* const wq = pin(ptrs.p[threadIdx.x >> 10]);
    const uint32_t tstart = now_ns();
    asm volatile("prefetch.tensormap [%0];" ::"l"(&tmWq) : "memory");
    asm volatile("prefetch.tensormap [%0];" ::"l"(&tmK) : "memory");
    if (threadIdx.x == 32)
        asm volatile("cp.async.bulk.prefetch.L2.global [%0], %1;" ::"l"(wq + blockIdx.x * PF_BYTES), "r"(PF_BYTES) : "memory");
    extern __shared__ __align__(1024) uint8_t smem_raw[];
    const uint32_t sb = pin((uint32_t)__cvta_generic_to_shared(smem_raw));
    if (threadIdx.x == 0) {
        mbar_init(sb + BAR_W, 1);
        asm volatile("fence.mbarrier_init.release.cluster;" ::: "memory");
        mbar_expect_tx(sb + BAR_W, 65536);
        tma2d(sb + OFF_WQ, &tmWq, blockIdx.x * 32, 0, sb + BAR_W);
        tma2d(sb + OFF_WQ + 16384, &tmWq, blockIdx.x * 32, 256, sb + BAR_W);
        tma3d(sb + OFF_X, &tmX, 0, 0, 0, sb + BAR_W);
    }
    const int warp = __shfl_sync(0xffffffffu, threadIdx.x >> 5, 0), lane = pin(threadIdx.x & 31);
    const int cta = pin(blockIdx.x), rank = cta & 1, bh = cta >> 1;

    if (warp == 8) {
        const int row0 = bh * 2048 + rank * 64;
        uint64_t pol;
        asm volatile("createpolicy.fractional.L2::evict_first.b64 %0, 1.0;" : "=l"(pol));
        auto issue = [&](int n) {
            const bool isv = n >= 2 * NT - KA || (n >= KA && ((n - KA) & 1));
            const int t = n < KA ? n : n >= 2 * NT - KA ? n - NT : isv ? (n - KA) >> 1 : (n + KA) >> 1;
            const int st = n % NST;
            if (isv) tma2d_hint(sb + st * STAGE, &tmV, rank * 64, bh * 2048 + t * 128, sb + BAR_FULL + 8 * st, pol);
            else tma3d_hint(sb + st * STAGE, &tmK, 0, row0 + t * 128, 0, sb + BAR_FULL + 8 * st, pol);
        };
        if (lane == 0) {
            if (sb & 1023) __trap();
#pragma unroll
            for (int i = 0; i < WIN0; i++) mbar_init(sb + BAR_FULL + 8 * i, 1);
            asm volatile("fence.mbarrier_init.release.cluster;" ::: "memory");
#pragma unroll
            for (int n = 0; n < WIN0; n++) {
                mbar_expect_tx(sb + BAR_FULL + 8 * n, STAGE);
                issue(n);
            }
            for (int i = WIN0; i < NST; i++) mbar_init(sb + BAR_FULL + 8 * i, 1);
            for (int i = 0; i < NST; i++) mbar_init(sb + BAR_EMPTY + 8 * i, 4);
            for (int i = 0; i < NP; i++) {
                mbar_init(sb + BAR_PFULL + 8 * i, 4);
                mbar_init(sb + BAR_PFULL + 8 * (NP + i), 1);
                mbar_expect_tx(sb + BAR_PFULL + 8 * (NP + i), 2048 + 64);
                mbar_init(sb + BAR_PEMPTY + 8 * i, 2);
                mbar_init(sb + BAR_PEMPTY + 8 * (NP + i), 2);
            }
            mbar_init(sb + BAR_STAT, 1);
            mbar_init(sb + BAR_F, 1);
            mbar_init(sb + BAR_D, 4);
            mbar_expect_tx(sb + BAR_STAT, 128);
            for (int i = 0; i < 4; i++) {
                mbar_init(sb + BAR_WO + 8 * i, 1);
                mbar_expect_tx(sb + BAR_WO + 8 * i, 8192);
            }
            asm volatile("fence.mbarrier_init.release.cluster;" ::: "memory");
            asm volatile("prefetch.tensormap [%0];" ::"l"(&tmWo) : "memory");
        }
        __syncwarp();
        asm volatile("bar.arrive 0, 288;" ::: "memory");
        asm volatile("barrier.cluster.arrive.relaxed.aligned;" ::: "memory");
        if (lane == 0) {
            auto wait_free = [&](int n) {
                const int st = n % NST, k = n / NST;
                if (st >= NST0) mbar_wait(sb + BAR_EMPTY + 8 * st, k & 1);
                else if (k) mbar_wait(sb + BAR_EMPTY + 8 * st, (k - 1) & 1);
            };
            const uint32_t t3 = tstart + PA_NS;
#pragma unroll
            for (int n = WIN0; n < 2 * NT; n++) {
                wait_free(n);
                mbar_expect_tx(sb + BAR_FULL + 8 * (n % NST), STAGE);
                if (n < WSW || n >= WSW + WIN - WIN0) {
                    const int d = n - (n < WSW ? WIN0 : WIN);
                    mbar_wait(sb + BAR_FULL + 8 * (d % NST), (d / NST) & 1);
                }
                if (n >= WSW) wait_until(t3 + (n - 3) * slot_ns);
                issue(n);
            }
#pragma unroll
            for (int n = 2 * NT; n < 2 * NT + 4; n++) wait_free(n);
#pragma unroll
            for (int g = 0; g < 4; g++) {
                wait_until(t3 + (WO_SLOT + g * WO_STEP) * slot_ns / 100);
                tma2d(sb + OFF_WO + g * 8192, &tmWo, (cta & 15) * 32, (cta >> 4) * 512 + g * 128, sb + BAR_WO + 8 * g);
            }
        }
        return;
    }

    unsigned epoch;
    asm volatile("ld.relaxed.gpu.global.u32 %0, [%1];" : "=r"(epoch) : "l"(&g_scr.ticket) : "memory");
    epoch >>= 7;
    if (cta < 16 && warp >= 4) {
        const int i = threadIdx.x - 128;
        *reinterpret_cast<uint4*>(out + (i >> 2) * 512 + cta * 32 + (i & 3) * 8) = make_uint4(0, 0, 0, 0);
    }
    const int g8 = lane >> 2, quad = lane & 3;
    const int rh = warp >> 2, g = (warp + 2 * rh) & 3;
    const uint4* const oin = pin(&g_scr.o[((cta >> 4) * 4 + g) * 512 + rh * 64 + lane]);
    uint4* const mine = pin(warp < 4 ? &g_scr.q[cta * 128 + warp * 32 + lane]
                                     : &g_scr.o[(((bh & 7) * 4 + (warp & 2) + (lane >> 4)) * 4 + rank * 2 + (warp & 1)) * 128 +
                                                (bh >> 3) * 16 + (lane & 15)]);
    __nv_bfloat16* const optr = pin(out + (rh * 16 + g * 4 + (lane >> 3)) * 512 + (cta & 15) * 32 + (lane & 7) * 4);
    bar_sync(0, 288);

    {
        const int kq = warp & 3, mt = warp >> 2;
        float c[4][4];
#pragma unroll
        for (int j = 0; j < 4; j++) c[j][0] = c[j][1] = c[j][2] = c[j][3] = 0.f;
        const int ar = mt * 16 + (lane & 15);
        const uint32_t abase = sb + OFF_X + kq * 8192 + ar * 128;
        const int br = lane & 15;
        const uint32_t bbase = sb + OFF_WQ + (kq * 128 + br) * 64;
        pkt_store(mine, 0, 0, 0, 0, epoch & 1);
        mbar_wait(sb + BAR_W, 0);
#pragma unroll
        for (int ks = 0; ks < 8; ks++) {
            uint32_t a[4], b0[4], b1[4];
            ldsm4(a, abase + (ks >> 2) * 4096 + ((((ks & 3) * 2 + (lane >> 4)) ^ (ar & 7)) << 4));
            ldsm4t(b0, bbase + ks * 1024 + (((lane >> 4) ^ ((br >> 1) & 3)) << 4));
            ldsm4t(b1, bbase + ks * 1024 + (((2 + (lane >> 4)) ^ ((br >> 1) & 3)) << 4));
            mma(c[0], a, b0[0], b0[1]);
            mma(c[1], a, b0[2], b0[3]);
            mma(c[2], a, b1[0], b1[1]);
            mma(c[3], a, b1[2], b1[3]);
        }
        bar_sync(1, 256);
        asm volatile("barrier.cluster.arrive.relaxed.aligned;" ::: "memory");
        const uint32_t rb = sb + OFF_QRED + (kq * 2 + mt) * 2048 + lane * 16;
        sts128f(rb, c[0][0], c[0][1], c[1][0], c[1][1]);
        sts128f(rb + 512, c[2][0], c[2][1], c[3][0], c[3][1]);
        sts128f(rb + 1024, c[0][2], c[0][3], c[1][2], c[1][3]);
        sts128f(rb + 1536, c[2][2], c[2][3], c[3][2], c[3][3]);
        bar_sync(1, 256);
    }
    const uint32_t tag = pin((epoch + 1) & 1);

    if (warp < 4) {
        {
            const uint32_t rb = sb + OFF_QRED + warp * 1024 + lane * 16;
            float4 s0 = lds128f(rb), s1 = lds128f(rb + 512);
#pragma unroll
            for (int kq = 1; kq < 4; kq++) {
                float4 t0 = lds128f(rb + kq * 4096), t1 = lds128f(rb + kq * 4096 + 512);
                s0.x += t0.x; s0.y += t0.y; s0.z += t0.z; s0.w += t0.w;
                s1.x += t1.x; s1.y += t1.y; s1.z += t1.z; s1.w += t1.w;
            }
            pkt_store(mine, pack_bf16_tagged(s0.x, s0.y, tag), pack_bf16(s0.z, s0.w),
                      pack_bf16_tagged(s1.x, s1.y, tag), pack_bf16(s1.z, s1.w), tag);
            __syncwarp();
            if (lane < NST - NST0) mbar_arrive(sb + BAR_EMPTY + 8 * (NST0 + lane));
        }
        __nanosleep(Q_DELAY_NS);
        uint32_t q[8][4];
        {
            const uint4* qp =
                &g_scr.q[(((bh & 7) * 4 + (warp & 2) + (lane >> 4)) * 4 + (warp & 1) * 2) * 128 + (bh >> 3) * 16 + (lane & 15)];
            Pkt u0, u1;
            pkt_load(u0, qp);
            pkt_load(u1, qp + 128);
#pragma unroll 1
            for (int it = 0;; it++) {
                const uint32_t b0 = u0.bad(tag), b1 = u1.bad(tag);
                if (!any_bit0(or3(b0, b1, 0u))) break;
                pkt_reload(u0, qp, b0);
                pkt_reload(u1, qp + 128, b1);
                if (it > (1 << 20)) __trap();
            }
            sts128(sb + OFF_P + warp * 1024 + lane * 16, u0.w0(), u0.w1(), u0.w2(), u0.w3());
            sts128(sb + OFF_P + warp * 1024 + 512 + lane * 16, u1.w0(), u1.w1(), u1.w2(), u1.w3());
            bar_sync(2, 128);
            Pkt v[8];
#pragma unroll
            for (int i = 0; i < 8; i++)
                asm volatile("ld.shared.v2.b64 {%0, %1}, [%2];"
                             : "=l"(v[i].lo), "=l"(v[i].hi) : "r"(sb + OFF_P + i * 512 + lane * 16) : "memory");
#pragma unroll
            for (int dq = 0; dq < 4; dq++) {
                const Pkt &a = v[dq], &b = v[4 + dq];
                q[2 * dq][0] = a.w0();     q[2 * dq][1] = b.w0();     q[2 * dq][2] = a.w1();     q[2 * dq][3] = b.w1();
                q[2 * dq + 1][0] = a.w2(); q[2 * dq + 1][1] = b.w2(); q[2 * dq + 1][2] = a.w3(); q[2 * dq + 1][3] = b.w3();
            }
        }
        asm volatile("barrier.cluster.wait.acquire.aligned;" ::: "memory");
        constexpr float C = 0.08838834764831845f * 1.4426950408889634f;
        float mc0 = -INFINITY, mc1 = -INFINITY, l0 = 0.f, l1 = 0.f;
        const int key = warp * 16 + (lane >> 4) * 8 + (lane & 7);
        const uint32_t koff = key * 128;
        const int ksel = (lane >> 3) & 1, kx = lane & 7;
        const uint32_t rp = mapa(sb + OFF_P + NP * 2048 + warp * 512 + lane * 16, rank ^ 1);
        const uint32_t ra = mapa(sb + OFF_ALPHA + NP * 64 + g8 * 4, rank ^ 1), rfull = mapa(sb + BAR_PFULL + 8 * NP, rank ^ 1);
        int st = 0;
        uint32_t par = 0;
#pragma unroll 1
        for (int i = 0; i < NT; i++) {
            const uint32_t kb = sb + st * STAGE + koff;
            float s[2][2][4];
#pragma unroll
            for (int j = 0; j < 4; j++) s[0][0][j] = s[0][1][j] = s[1][0][j] = s[1][1][j] = 0.f;
            mbar_wait(sb + BAR_FULL + 8 * st, par);
#pragma unroll
            for (int ks = 0; ks < 8; ks++) {
                uint32_t b[4];
                ldsm4(b, kb + (ks >> 2) * 8192 + ((((ks & 3) * 2 + ksel) ^ kx) << 4));
                mma(s[ks & 1][0], q[ks], b[0], b[1]);
                mma(s[ks & 1][1], q[ks], b[2], b[3]);
            }
            __syncwarp();
            if (lane == 0) mbar_arrive(sb + BAR_EMPTY + 8 * st);
            st += i < KA ? 1 : 2;
            if (st >= NST) { st -= NST; par ^= 1; }
            float sv[2][4];
#pragma unroll
            for (int j = 0; j < 4; j++) { sv[0][j] = s[0][0][j] + s[1][0][j]; sv[1][j] = s[0][1][j] + s[1][1][j]; }
            float t0 = fmaxf(fmaxf(sv[0][0], sv[0][1]), fmaxf(sv[1][0], sv[1][1]));
            float t1 = fmaxf(fmaxf(sv[0][2], sv[0][3]), fmaxf(sv[1][2], sv[1][3]));
            t0 = fmaxf(t0, __shfl_xor_sync(0xffffffffu, t0, 1));
            t1 = fmaxf(t1, __shfl_xor_sync(0xffffffffu, t1, 1));
            t0 = fmaxf(t0, __shfl_xor_sync(0xffffffffu, t0, 2));
            t1 = fmaxf(t1, __shfl_xor_sync(0xffffffffu, t1, 2));
            const uint32_t wm = sb + OFF_WMAX + (i & 1) * 256 + g8 * 16;
            if (quad == 0) { sts32f(wm + warp * 4, t0); sts32f(wm + 128 + warp * 4, t1); }
            bar_sync(2, 128);
            const float4 w0 = lds128f(wm), w1 = lds128f(wm + 128);
            const float n0 = fmaxf(mc0, fmaxf(fmaxf(w0.x, w0.y), fmaxf(w0.z, w0.w)) * C);
            const float n1 = fmaxf(mc1, fmaxf(fmaxf(w1.x, w1.y), fmaxf(w1.z, w1.w)) * C);
            const float a0 = ex2(mc0 - n0), a1 = ex2(mc1 - n1);
            mc0 = n0; mc1 = n1;
            float p[2][4];
#pragma unroll
            for (int j = 0; j < 2; j++) {
                p[j][0] = ex2(fmaf(sv[j][0], C, -n0)); p[j][1] = ex2(fmaf(sv[j][1], C, -n0));
                p[j][2] = ex2(fmaf(sv[j][2], C, -n1)); p[j][3] = ex2(fmaf(sv[j][3], C, -n1));
            }
            l0 = l0 * a0 + ((p[0][0] + p[0][1]) + (p[1][0] + p[1][1]));
            l1 = l1 * a1 + ((p[0][2] + p[0][3]) + (p[1][2] + p[1][3]));
            const int slot = i % NP;
            if (i >= NP) {
                mbar_wait(sb + BAR_PEMPTY + 8 * slot, (i / NP - 1) & 1);
                mbar_wait(sb + BAR_PEMPTY + 8 * (NP + slot), (i / NP - 1) & 1);
            }
            const uint32_t p0 = pack_bf16(p[0][0], p[0][1]), p1 = pack_bf16(p[0][2], p[0][3]), p2 = pack_bf16(p[1][0], p[1][1]),
                           p3 = pack_bf16(p[1][2], p[1][3]);
            asm volatile("st.async.weak.shared::cluster.mbarrier::complete_tx::bytes.v4.b32 [%0], {%1,%2,%3,%4}, [%5];"
                         ::"r"(rp + slot * 2048), "r"(p1), "r"(p0), "r"(p3), "r"(p2), "r"(rfull + 8 * slot) : "memory");
            sts128(sb + OFF_P + slot * 2048 + warp * 512 + lane * 16, p0, p1, p2, p3);
            if (warp == 0 && quad == 0) {
                asm volatile("st.async.weak.shared::cluster.mbarrier::complete_tx::bytes.f32 [%0], %1, [%2];"
                             ::"r"(ra + slot * 64), "f"(a1), "r"(rfull + 8 * slot) : "memory");
                asm volatile("st.async.weak.shared::cluster.mbarrier::complete_tx::bytes.f32 [%0], %1, [%2];"
                             ::"r"(ra + slot * 64 + 32), "f"(a0), "r"(rfull + 8 * slot) : "memory");
                sts32f(sb + OFF_ALPHA + slot * 64 + g8 * 4, a0);
                sts32f(sb + OFF_ALPHA + slot * 64 + 32 + g8 * 4, a1);
            }
            __syncwarp();
            if (lane == 0) mbar_arrive(sb + BAR_PFULL + 8 * slot);
        }
        l0 += __shfl_xor_sync(0xffffffffu, l0, 1);
        l1 += __shfl_xor_sync(0xffffffffu, l1, 1);
        l0 += __shfl_xor_sync(0xffffffffu, l0, 2);
        l1 += __shfl_xor_sync(0xffffffffu, l1, 2);
        if (quad == 0) {
            sts32f(sb + OFF_LSUM + g8 * 16 + warp * 4, l0);
            sts32f(sb + OFF_LSUM + 128 + g8 * 16 + warp * 4, l1);
            if (warp == 0) { sts32f(sb + OFF_MROW + g8 * 4, mc0); sts32f(sb + OFF_MROW + 32 + g8 * 4, mc1); }
        }
        bar_sync(2, 128);
        if (warp == 0) {
            if (lane < 16) {
                const float4 lv = lds128f(sb + OFF_LSUM + lane * 16);
                const float l = (lv.x + lv.y) + (lv.z + lv.w), m = lds32f(sb + OFF_MROW + lane * 4);
                asm volatile("st.async.weak.shared::cluster.mbarrier::complete_tx::bytes.v2.f32 [%0], {%1,%2}, [%3];"
                             ::"r"(mapa(sb + OFF_STAT + lane * 8, rank ^ 1)), "f"(m), "f"(l), "r"(mapa(sb + BAR_STAT, rank ^ 1)) : "memory");
                mbar_wait(sb + BAR_STAT, 0);
                const float pm = lds32f(sb + OFF_STAT + lane * 8), pl = lds32f(sb + OFF_STAT + lane * 8 + 4);
                const float mm = fmaxf(m, pm);
                const float e = ex2(m - mm), pe = ex2(pm - mm);
                const float inv = __fdividef(1.f, rank ? pl * pe + l * e : l * e + pl * pe);
                sts32f(sb + OFF_F + lane * 4, e * inv);
                sts32f(sb + OFF_F + 64 + (lane ^ 8) * 4, pe * inv);
            }
            __syncwarp();
            if (lane == 0) mbar_arrive(sb + BAR_F);
        }
        mbar_wait(sb + BAR_D, 0);
    } else {
        const int w = warp - 4;
        asm volatile("barrier.cluster.wait.acquire.aligned;" ::: "memory");
        if (threadIdx.x == 128) {
            asm volatile("red.relaxed.gpu.global.add.u32 [%0], 1;" ::"l"(&g_scr.ticket) : "memory");
            if (cta < 16) asm volatile("st.release.gpu.global.u32 [%0], %1;" ::"l"(&g_scr.zeroed[cta * 32]), "r"(epoch + 1) : "memory");
            unsigned z;
#pragma unroll 1
            for (int it = 0;; it++) {
                asm volatile("ld.acquire.gpu.global.u32 %0, [%1];" : "=r"(z) : "l"(&g_scr.zeroed[(cta & 15) * 32]) : "memory");
                if (z == epoch + 1) break;
                if (it > (1 << 20)) __trap();
                __nanosleep(200);
            }
        }
        __syncwarp();
        const int src = w >> 1, ds = w & 1;
        const uint32_t pbase = pin(sb + OFF_P + src * NP * 2048 + lane * 16), abase = pin(sb + OFF_ALPHA + src * NP * 64 + g8 * 4);
        const uint32_t pfull = pin(sb + BAR_PFULL + src * NP * 8);
        const uint32_t pempty = src ? mapa(sb + BAR_PEMPTY + 8 * NP, rank ^ 1) : mapa(sb + BAR_PEMPTY, rank);
        float o[4][4], t[2][4][4];
#pragma unroll
        for (int j = 0; j < 16; j++) (&o[0][0])[j] = (&t[0][0][0])[j] = (&t[1][0][0])[j] = 0.f;
        const uint32_t voff = ((rank ^ src) * 64 + (lane & 15)) * 128;
        const int vc = ds * 4 + (lane >> 4), vx = lane & 7;
        const uint32_t v0 = pin(sb + voff + ((vc ^ vx) << 4)), v1 = pin(sb + voff + (((vc + 2) ^ vx) << 4));
        uint32_t p[4][4], b0[4][4], b1[4][4];
        float a0 = 0.f, a1 = 0.f;
        auto load_v = [&](int st) {
#pragma unroll
            for (int j = 0; j < 4; j++) {
                ldsm4t(b0[j], v0 + st * STAGE + j * 2048);
                ldsm4t(b1[j], v1 + st * STAGE + j * 2048);
            }
        };
        auto next_p = [&](int i) {
            const int slot = i % NP;
            mbar_wait(pfull + 8 * slot, (i / NP) & 1);
#pragma unroll
            for (int j = 0; j < 4; j++) lds128(p[j], pbase + slot * 2048 + j * 512);
            const float n0 = lds32f(abase + slot * 64), n1 = lds32f(abase + slot * 64 + 32);
            __syncwarp();
            if (lane == 0 && i < NT - NP) {
                if (w == 2) mbar_expect_tx(pfull + 8 * slot, 2048 + 64);
                asm volatile("mbarrier.arrive.relaxed.cluster.shared::cluster.b64 _, [%0];"
                             ::"r"(pempty + 8 * slot + ((p[3][3] | __float_as_uint(n1)) & zero)) : "memory");
            }
#pragma unroll
            for (int j = 0; j < 4; j++) {
                o[j][0] = fmaf(o[j][0], a0, t[0][j][0] + t[1][j][0]); o[j][1] = fmaf(o[j][1], a0, t[0][j][1] + t[1][j][1]);
                o[j][2] = fmaf(o[j][2], a1, t[0][j][2] + t[1][j][2]); o[j][3] = fmaf(o[j][3], a1, t[0][j][3] + t[1][j][3]);
            }
            a0 = n0; a1 = n1;
        };
        auto pv = [&]() {
#pragma unroll
            for (int j = 0; j < 16; j++) (&t[0][0][0])[j] = (&t[1][0][0])[j] = 0.f;
#pragma unroll
            for (int j = 0; j < 4; j++) {
                mma(t[j & 1][0], p[j], b0[j][0], b0[j][1]);
                mma(t[j & 1][1], p[j], b0[j][2], b0[j][3]);
                mma(t[j & 1][2], p[j], b1[j][0], b1[j][1]);
                mma(t[j & 1][3], p[j], b1[j][2], b1[j][3]);
            }
        };
        int st = KA + 1;
        uint32_t par = 0;
#pragma unroll 1
        for (int i = 0; i < NT - 1; i++) {
            mbar_wait(sb + BAR_FULL + 8 * st, par);
            load_v(st);
            next_p(i);
            pv();
            __syncwarp();
            if (lane == 0) mbar_arrive(sb + BAR_EMPTY + 8 * st);
            st += i < NT - KA - 1 ? 2 : 1;
            if (st >= NST) { st -= NST; par ^= 1; }
        }
        constexpr int LST = (2 * NT - 1) % NST, LPAR = ((2 * NT - 1) / NST) & 1;
        const bool landed = mbar_test(sb + BAR_FULL + 8 * LST, LPAR);
        if (landed) load_v(LST);
        next_p(NT - 1);
        mbar_wait(sb + BAR_F, 0);
        const float f0 = lds32f(sb + OFF_F + src * 64 + g8 * 4), f1 = lds32f(sb + OFF_F + src * 64 + 32 + g8 * 4);
        a0 *= f0; a1 *= f1;
#pragma unroll
        for (int j = 0; j < 4; j++) {
            o[j][0] *= a0; o[j][1] *= a0; o[j][2] *= a1; o[j][3] *= a1;
            asm volatile("" : "+f"(o[j][0]), "+f"(o[j][1]), "+f"(o[j][2]), "+f"(o[j][3]));
        }
        if (!landed) {
            mbar_wait(sb + BAR_FULL + 8 * LST, LPAR);
            load_v(LST);
        }
        pv();
#pragma unroll
        for (int j = 0; j < 4; j++) {
            o[j][0] = fmaf(t[0][j][0] + t[1][j][0], f0, o[j][0]); o[j][1] = fmaf(t[0][j][1] + t[1][j][1], f0, o[j][1]);
            o[j][2] = fmaf(t[0][j][2] + t[1][j][2], f1, o[j][2]); o[j][3] = fmaf(t[0][j][3] + t[1][j][3], f1, o[j][3]);
        }
        {
            const uint32_t ours = sb + OFF_MERGE + w * 1024 + lane * 16, theirs = sb + OFF_MERGE + (w ^ 2) * 1024 + lane * 16;
            sts128f(theirs, o[0][2], o[0][3], o[1][2], o[1][3]);
            sts128f(theirs + 512, o[2][2], o[2][3], o[3][2], o[3][3]);
            bar_sync(5 + ds, 64);
            const float4 r0 = lds128f(ours), r1 = lds128f(ours + 512);
            pkt_store(mine, pack_bf16(o[0][0] + r0.x, o[0][1] + r0.y), pack_bf16(o[1][0] + r0.z, o[1][1] + r0.w),
                      pack_bf16(o[2][0] + r1.x, o[2][1] + r1.y), pack_bf16(o[3][0] + r1.z, o[3][1] + r1.w), tag);
        }
        if (lane == 0) mbar_arrive(sb + BAR_D);
    }

    {
        uint32_t a[8][2][4];
        const int kr = (lane >> 4) * 8 + (lane & 7);
        const int wc = (lane >> 3) & 1, wx = (kr >> 1) & 3;
        const uint32_t wb0 = pin(sb + OFF_WO + (g * 128 + kr) * 64 + ((wc ^ wx) << 4));
        const uint32_t wb1 = pin(sb + OFF_WO + (g * 128 + kr) * 64 + (((wc + 2) ^ wx) << 4));
        const uint32_t rw = pin(sb + OFF_PRED + (rh * 4 + g) * 2304 + quad * 288 + g8 * 4);
        const uint32_t rr = pin(sb + OFF_PRED + rh * 4 * 2304 + (g * 4 + (lane >> 3)) * 144 + (lane & 7) * 16);
        const uint32_t wobar = sb + BAR_WO + 8 * g;
        constexpr uint32_t wopar = 0;
        auto wo_within = [&](uint32_t clks) {
            uint32_t c0, c1;
            bool in;
            asm volatile("mov.u32 %0, %%clock;" : "=r"(c0));
            do {
                in = mbar_test(wobar, wopar);
                asm volatile("mov.u32 %0, %%clock;" : "=r"(c1));
            } while (!in && c1 - c0 < clks);
            return in;
        };
        Pkt v[8];
        const bool in0 = wo_within(O_DELAY);
        pkt_issue<8, 4, 128, 32>(v, oin);
        if (!in0) {
#pragma unroll 1
            for (int it = 0; !wo_within(O_PERIOD); it++) {
                uint32_t b[8];
#pragma unroll
                for (int i = 0; i < 8; i++) b[i] = v[i].bad(tag);
                if (it > (1 << 16)) __trap();
#pragma unroll
                for (int i = 0; i < 8; i++) pkt_reload(v[i], oin + (i >> 2) * 32 + (i & 3) * 128, b[i]);
            }
        }
#pragma unroll
        for (int ks = 0; ks < 8; ks++) {
            ldsm4t(a[ks][0], wb0 + ks * 1024);
            ldsm4t(a[ks][1], wb1 + ks * 1024);
        }
        pkt_poll<8, 4, 128, 32>(v, oin, tag | (a[7][1][3] & zero));
        float c[2][2][4];
#pragma unroll
        for (int j = 0; j < 16; j++) (&c[0][0][0])[j] = 0.f;
#pragma unroll
        for (int ks = 0; ks < 8; ks++)
#pragma unroll
            for (int t = 0; t < 2; t++) {
                const Pkt& pk = v[t * 4 + (ks >> 1)];
                mma(c[t][0], a[ks][0], ks & 1 ? pk.w2() : pk.w0(), ks & 1 ? pk.w3() : pk.w1());
                mma(c[t][1], a[ks][1], ks & 1 ? pk.w2() : pk.w0(), ks & 1 ? pk.w3() : pk.w1());
            }
#pragma unroll
        for (int t = 0; t < 2; t++)
#pragma unroll
            for (int mt = 0; mt < 2; mt++)
#pragma unroll
                for (int e = 0; e < 4; e++) sts32f(rw + (t * 8 + (e & 1)) * 144 + (mt * 16 + (e >> 1) * 8) * 4, c[t][mt][e]);
        bar_sync(3 + rh, 128);
        const float4 s0 = lds128f(rr), s1 = lds128f(rr + 2304), s2 = lds128f(rr + 2 * 2304), s3 = lds128f(rr + 3 * 2304);
        asm volatile("red.relaxed.gpu.global.add.noftz.v2.bf16x2 [%0], {%1, %2};"
                     ::"l"(optr), "r"(pack_bf16((s0.x + s1.x) + (s2.x + s3.x), (s0.y + s1.y) + (s2.y + s3.y))),
                       "r"(pack_bf16((s0.z + s1.z) + (s2.z + s3.z), (s0.w + s1.w) + (s2.w + s3.w))) : "memory");
    }
}

__global__ void fb_proj(const __nv_bfloat16* a_bf, const float* a_f, const __nv_bfloat16* w, int K, int N, float* o_f,
                        __nv_bfloat16* o_bf) {
    const int c = blockIdx.x * blockDim.x + threadIdx.x, r = blockIdx.y;
    float s = 0.f;
    for (int k = 0; k < K; k++) s += (a_bf ? __bfloat162float(a_bf[r * K + k]) : a_f[r * K + k]) * __bfloat162float(w[k * N + c]);
    if (o_bf) o_bf[r * N + c] = __float2bfloat16(s);
    else o_f[r * N + c] = __bfloat162float(__float2bfloat16(s));
}
__global__ void fb_attn(const __nv_bfloat16* kc, const __nv_bfloat16* vc) {
    __shared__ float sc[2048], red[128];
    const int r = blockIdx.x, hq = blockIdx.y, t = threadIdx.x;
    const size_t base = (size_t)((r >> 2) * 8 + (hq >> 2)) * 2048 * 128;
    float m = -INFINITY, l = 0.f, acc = 0.f;
    for (int j = t; j < 2048; j += 128) {
        float s = 0.f;
        for (int d = 0; d < 128; d++) s += g_scr.fq[r * 4096 + hq * 128 + d] * __bfloat162float(kc[base + j * 128 + d]);
        sc[j] = s * 0.08838834764831845f;
        m = fmaxf(m, sc[j]);
    }
    red[t] = m;
    __syncthreads();
    for (int i = 0; i < 128; i++) m = fmaxf(m, red[i]);
    for (int j = t; j < 2048; j += 128) sc[j] = __expf(sc[j] - m);
    __syncthreads();
    for (int j = 0; j < 2048; j++) {
        l += sc[j];
        acc += sc[j] * __bfloat162float(vc[base + j * 128 + t]);
    }
    g_scr.fo[r * 4096 + hq * 128 + t] = __bfloat162float(__float2bfloat16(acc / l));
}

typedef CUresult (*EncodeFn)(CUtensorMap*, CUtensorMapDataType, cuuint32_t, void*, const cuuint64_t*, const cuuint64_t*,
                             const cuuint32_t*, const cuuint32_t*, CUtensorMapInterleave, CUtensorMapSwizzle,
                             CUtensorMapL2promotion, CUtensorMapFloatOOBfill);

static void encode(EncodeFn fn, CUtensorMap* m, void* p, int rank, const cuuint64_t* dims, const cuuint64_t* strides,
                   const cuuint32_t* box, CUtensorMapSwizzle sw) {
    const cuuint32_t es[3] = {1, 1, 1};
    fn(m, CU_TENSOR_MAP_DATA_TYPE_BFLOAT16, rank, p, dims, strides, box, es, CU_TENSOR_MAP_INTERLEAVE_NONE, sw,
       CU_TENSOR_MAP_L2_PROMOTION_L2_256B, CU_TENSOR_MAP_FLOAT_OOB_FILL_NONE);
}

}

extern "C" void kernel_launch(void* const* d_in, const int* in_sizes, int n_in, void* d_out, int out_size) {
    using namespace gqa;
    static EncodeFn fn = nullptr;
    static uint32_t slot_ns = SLOT_NS;
    static bool fits = false;
    if (!fn) {
        int dev = 0, khz = 0, bits = 0;
        cudaGetDevice(&dev);
        cudaDeviceGetAttribute(&khz, cudaDevAttrMemoryClockRate, dev);
        cudaDeviceGetAttribute(&bits, cudaDevAttrGlobalMemoryBusWidth, dev);
        if (khz > 0 && bits > 0) slot_ns = (uint32_t)((double)NCTA * STAGE / (0.955 * 2.0 * khz * 1e-6 * (bits / 8)));
        void* p = nullptr;
        cudaDriverEntryPointQueryResult qr;
        cudaGetDriverEntryPoint("cuTensorMapEncodeTiled", &p, cudaEnableDefault, &qr);
        fn = (EncodeFn)p;
        cudaFuncSetAttribute(gqa_kernel, cudaFuncAttributeMaxDynamicSharedMemorySize, SMEM_BYTES);
        cudaLaunchConfig_t cfg = {};
        cfg.gridDim = dim3(NCTA);
        cfg.blockDim = dim3(288);
        cfg.dynamicSmemBytes = SMEM_BYTES;
        int clusters = 0;
        fits = cudaOccupancyMaxActiveClusters(&clusters, gqa_kernel, &cfg) == cudaSuccess && clusters >= NCTA / 2;
    }
    if (!fits) {
        Scratch* scr = nullptr;
        cudaGetSymbolAddress((void**)&scr, g_scr);
        float *fq = scr->fq, *fo = scr->fo;
        fb_proj<<<dim3(16, 32), 256, 0, cudaStreamPerThread>>>((const __nv_bfloat16*)d_in[0], nullptr, (const __nv_bfloat16*)d_in[3], 512,
                                                               4096, fq, nullptr);
        fb_attn<<<dim3(32, 32), 128, 0, cudaStreamPerThread>>>((const __nv_bfloat16*)d_in[1], (const __nv_bfloat16*)d_in[2]);
        fb_proj<<<dim3(2, 32), 256, 0, cudaStreamPerThread>>>(nullptr, fo, (const __nv_bfloat16*)d_in[4], 4096, 512, nullptr,
                                                              (__nv_bfloat16*)d_out);
        return;
    }
    CUtensorMap tmK, tmV, tmX, tmWq, tmWo;
    {
        const cuuint64_t dims[3] = {64, 8 * 8 * 2048, 2}, str[2] = {256, 128};
        const cuuint32_t box[3] = {64, 64, 2};
        encode(fn, &tmK, d_in[1], 3, dims, str, box, CU_TENSOR_MAP_SWIZZLE_128B);
        const cuuint64_t dv[2] = {128, 8 * 8 * 2048}, sv[1] = {256};
        const cuuint32_t bv[2] = {64, 128};
        encode(fn, &tmV, d_in[2], 2, dv, sv, bv, CU_TENSOR_MAP_SWIZZLE_128B);
    }
    {
        const cuuint64_t dims[3] = {64, 32, 8}, str[2] = {1024, 128};
        const cuuint32_t box[3] = {64, 32, 8};
        encode(fn, &tmX, d_in[0], 3, dims, str, box, CU_TENSOR_MAP_SWIZZLE_128B);
    }
    {
        const cuuint64_t dq[2] = {4096, 512}, sq[1] = {8192}, dw[2] = {512, 4096}, sw[1] = {1024};
        const cuuint32_t box[2] = {32, 256};
        encode(fn, &tmWq, d_in[3], 2, dq, sq, box, CU_TENSOR_MAP_SWIZZLE_64B);
        const cuuint32_t boxo[2] = {32, 128};
        encode(fn, &tmWo, d_in[4], 2, dw, sw, boxo, CU_TENSOR_MAP_SWIZZLE_64B);
    }
    gqa_kernel<<<NCTA, 288, SMEM_BYTES, cudaStreamPerThread>>>(Ptrs{{(const uint8_t*)d_in[3], nullptr}}, (__nv_bfloat16*)d_out,
                                                               slot_ns, 0u, tmK, tmV, tmX, tmWq, tmWo);
}
```
